```python
import torch

def _softmax(x, axis=-1):
    return torch.softmax(x, dim=axis)

def _gelu(x):
    return torch.nn.functional.gelu(x, approximate='tanh')

def _silu(x):
    return torch.nn.functional.silu(x)

def _sigmoid(x):
    return torch.sigmoid(x)

def _layernorm(x, axis=-1, eps=1e-05):
    m = x.mean(dim=axis, keepdim=True)
    v = x.var(dim=axis, keepdim=True, unbiased=False)
    return (x - m) / torch.sqrt(v + eps)

def _scatter_add(tgt, idx, src, axis=0):
    return tgt.clone().index_add_(axis, idx, src)

def _segment_sum(src, seg, n):
    out = torch.zeros((n,) + src.shape[1:], dtype=src.dtype)
    return out.index_add_(0, seg, src)

def _pad(x, pw):
    flat = tuple((v for pair in reversed(pw) for v in pair))
    return torch.nn.functional.pad(x, flat)
kernel_name = 'adaLN_cond__sliding_block__mixer_gmlp__prompt'

def setup_inputs():

    _w = lambda a: (lambda t: t.to(torch.bfloat16) if t.is_floating_point() else t)(torch.as_tensor(a))

    def _A_setup():
        B, S, D = (1, 2048, 448)
        return {'x': _w((lambda *s: torch.randn(*s, dtype=torch.bfloat16) * 0.05)(B, S, D)), 'wqkv': _w((lambda *s: torch.randn(*s, dtype=torch.bfloat16) * 0.05)(D, 3 * D)), 'wo': _w((lambda *s: torch.randn(*s, dtype=torch.bfloat16) * 0.05)(D, D))}
    _A_in = _A_setup()

    def _B_setup():
        B, S, D, F = (1, 2048, 448, 1792)
        Fh = F // 2
        return {'x': _w((lambda *s: torch.randn(*s, dtype=torch.bfloat16) * 0.05)(B, S, D)), 'w_in': _w((lambda *s: torch.randn(*s, dtype=torch.bfloat16) * 0.4)(D, 2 * Fh)), 'w_sp': _w(0.01 * (lambda *s: torch.randn(*s, dtype=torch.bfloat16) * 0.4)(S, S)), 'b_sp': _w(1.0 + 0.01 * (lambda *s: torch.randn(*s, dtype=torch.bfloat16) * 0.05)(S)), 'w_out': _w((lambda *s: torch.randn(*s, dtype=torch.bfloat16) * 0.05)(Fh, D))}
    _B_in = _B_setup()
    return {'A_x': _A_in['x'], 'A_wqkv': _A_in['wqkv'], 'A_wo': _A_in['wo'], 'B_x': _B_in['x'], 'B_w_in': _B_in['w_in'], 'B_w_sp': _B_in['w_sp'], 'B_b_sp': _B_in['b_sp'], 'B_w_out': _B_in['w_out'], 'c': _w((lambda *s: torch.randn(*s, dtype=torch.bfloat16) * 0.1)(1, 448) * 8.0), 'w_mod': _w((lambda *s: torch.randn(*s, dtype=torch.bfloat16) * 0.1)(448, 6 * 448) * 448 ** (-0.5) * 8.0)}

def reference(A_x, A_wqkv, A_wo, B_x, B_w_in, B_w_sp, B_b_sp, B_w_out, c, w_mod):

    def _A_ref(x, wqkv, wo):
        B, S, D = x.shape
        H = 16
        Dh = D // H
        W = 256
        qkv = (lambda x, *d: x.permute(*d))((x @ wqkv).reshape(B, S, 3, H, Dh), 2, 0, 3, 1, 4)
        q, k, v = (qkv[0], qkv[1], qkv[2])
        scores = torch.einsum('bhqd,bhkd->bhqk', q, k) * Dh ** (-0.5)
        idx = torch.arange(S)
        mask = (idx[:, None] - idx[None, :] >= 0) & (idx[:, None] - idx[None, :] < W)
        scores = torch.where(mask[None, None], scores, -1000000000.0)
        p = _softmax(scores, axis=-1)
        o = torch.einsum('bhqk,bhkd->bhqd', p, v)
        return (lambda x, *d: x.permute(*d))(o, 0, 2, 1, 3).reshape(B, S, D) @ wo

    def _B_ref(x, w_in, w_sp, b_sp, w_out):
        B, S, D = x.shape
        F = w_in.shape[-1]
        Fh = F // 2
        z = _gelu(torch.einsum('bsd,df->bsf', x, w_in))
        z1 = z[..., :Fh].clone()
        z2 = _layernorm(z[..., Fh:], axis=-1)
        g = torch.einsum('ts,bsf->btf', w_sp, z2) + b_sp[None, :, None]
        return torch.einsum('bsf,fd->bsd', z1 * g, w_out)
    x = A_x
    mod = (_silu(c) @ w_mod).reshape(c.shape[0], 6, 1, -1)
    sa, ca, ga, sb, cb, gb = (mod[:, 0].clone(), mod[:, 1].clone(), mod[:, 2].clone(), mod[:, 3].clone(), mod[:, 4].clone(), mod[:, 5].clone())
    h = _layernorm(x, axis=-1) * (1 + ca) + sa
    x = x + ga * _A_ref(h, A_wqkv, A_wo)
    h = _layernorm(x, axis=-1) * (1 + cb) + sb
    x = x + gb * _B_ref(h, B_w_in, B_w_sp, B_b_sp, B_w_out)
    return x
```

```cpp
#include <cuda_runtime.h>
#include <cuda.h>
#include <cuda_bf16.h>
#include <stdint.h>

namespace {

constexpr int NTHREADS = 384;
constexpr int POLL_NS = 50, GATHER_NS = 50;
#define SMID_MAX 132u

constexpr uint32_t R0 = 0;
constexpr uint32_t R1 = 114688;
constexpr uint32_t MISC = 229376;
constexpr uint32_t TAB = MISC + 768;
constexpr uint32_t GTAB = TAB + 1792;
constexpr uint32_t TAGW = GTAB + 448;
constexpr uint32_t SMEM_BYTES = 232448;
constexpr uint32_t KVB = 15360;
constexpr uint32_t WM_BASE = R1 + 81920;
constexpr uint32_t WM2 = R1 + 100352, WM2_C = R0 + 6 * KVB;
constexpr uint32_t WS_IN = R1 + 71680, WS_PK = R1 + 57344;
constexpr uint32_t RT_A = R1 + 65536, RT_B = R1 + 86016;
constexpr uint32_t DSTAGE = 30720;
constexpr int DSTAGES = 7;
constexpr uint32_t WOUT_BASE = 114688;

enum {
    B_XF = 0, B_WKV = 5, B_WQ = 12, B_PUB = 13, B_ROLE = 14, B_WO = 15, B_OF = 16, B_WINF = 20, B_WINE = 24, B_X1F = 28,
    B_DF = 32, B_DE = 39, B_WOUT = 46, B_UE = 48, B_UF = 52, B_KVFREE = 60, B_KVPASS = 62, B_QPASS = 63,
    B_ATT = 64, B_C1D = 65, B_C2D = 66, B_DD = 67, B_STKV = 68, B_STO = 69, B_STX1 = 70, B_STZ2 = 71,
    B_STU = 72, B_HELP = 73, B_ORD = 74, B_TAG = 75, B_UV = 76, B_WS = 77, B_WMFREE = 78, B_RT = 79, B_WM = 80, B_C = 81, B_GO = 82, B_STW = 83, B_GT = 84, B_DONE = 85, B_KVN = 86, B_SMID = 90, B_LKV = 91, B_LO = 92, B_LX1 = 93, B_LU = 94, NBAR = 95
};
__host__ __device__ constexpr int bar_count(int i) {
    return (i >= B_WINE && i < B_WINE + 4) || (i >= B_KVFREE && i < B_KVFREE + 2) || i == B_WMFREE || i == B_HELP ? 2
         : (i >= B_DE && i < B_DE + 7) ? 4
         : (i >= B_UE && i < B_UE + 4) ? 4
         : (i == B_KVPASS || i == B_QPASS || i == B_STW || i == B_DONE || i >= B_LKV || (i >= B_STKV && i <= B_STU)) ? 8
         : (i >= B_C1D && i <= B_DD) ? 16
         : i == B_ATT ? 16 : 1;
}
enum { F_KV = 0, F_O = 1, F_X1 = 2, F_Z2 = 3, F_U = 4, F_R1 = 5, F_R2 = 6, F_R3 = 7, F_WP = 8, NFLAG = 9 };

struct Params {
    CUtensorMap wmod, x, wqkv, wo, wsp, wout, out, wins, wmod16;
    const __nv_bfloat16 *c, *bsp, *wsp_p;
    unsigned char role[68];
};

__device__ uint32_t g_epoch;
__device__ __align__(128) uint2 g_here[64];
__device__ __align__(128) uint2 g_modp[2688 + 896];
__device__ __align__(128) uint32_t g_flag[NFLAG * 128 * 8];
__device__ __align__(128) uint4 g_st[3][32 * 8 * 64];
__device__ __align__(128) float4 g_uv[896];
__device__ __align__(1024) unsigned char g_wkv[8 * 7 * 14336];
__device__ __align__(1024) unsigned char g_wq[8 * 7 * 7168];
__device__ __align__(1024) unsigned char g_wo[8 * 4 * 14336];
__device__ __align__(1024) unsigned char g_wout[8 * 8 * 14336];
__device__ __align__(1024) unsigned char g_winp[16 * 4 * 25088];
__device__ __align__(1024) unsigned char g_kv[32 * 8 * KVB];
__device__ __align__(1024) unsigned char g_o[32 * 8 * 7168];
__device__ __align__(1024) unsigned char g_x1[32 * 8 * 7168];
__device__ __align__(1024) unsigned char g_z2n[8 * 32 * 14336];
__device__ __align__(1024) unsigned char g_u[32 * 8 * 14336];
#define TS(i) do {} while (0)

__device__ __forceinline__ uint32_t smem_u32(const void* p) { return (uint32_t)__cvta_generic_to_shared(p); }
__device__ __forceinline__ void mbar_init(uint32_t bar, uint32_t cnt) { asm volatile("mbarrier.init.shared::cta.b64 [%0], %1;" ::"r"(bar), "r"(cnt)); }
__device__ __forceinline__ void mbar_expect_tx(uint32_t bar, uint32_t bytes) { asm volatile("mbarrier.arrive.expect_tx.shared::cta.b64 _, [%0], %1;" ::"r"(bar), "r"(bytes) : "memory"); }
__device__ __forceinline__ void mbar_arrive(uint32_t bar) { asm volatile("mbarrier.arrive.shared::cta.b64 _, [%0];" ::"r"(bar) : "memory"); }
__device__ __forceinline__ void mbar_arrive_cl(uint32_t cluster_addr) { asm volatile("mbarrier.arrive.shared::cluster.b64 _, [%0];" ::"r"(cluster_addr) : "memory"); }
__device__ __forceinline__ uint32_t mapa(uint32_t addr, uint32_t cta) { uint32_t r; asm volatile("mapa.shared::cluster.u32 %0, %1, %2;" : "=r"(r) : "r"(addr), "r"(cta)); return r; }
__device__ __forceinline__ bool mbar_test(uint32_t bar, uint32_t parity) {
    uint32_t ok;
    asm volatile("{\n.reg .pred p;\nmbarrier.test_wait.parity.shared::cta.b64 p, [%1], %2;\nselp.u32 %0, 1, 0, p;\n}" : "=r"(ok) : "r"(bar), "r"(parity) : "memory");
    return ok;
}
__device__ __forceinline__ void mbar_wait(uint32_t bar, uint32_t parity) {
    asm volatile("{\n.reg .pred p;\n.reg .u32 n;\nmov.u32 n, 0;\nW%=:\nmbarrier.try_wait.parity.shared::cta.b64 p, [%0], %1;\n@p bra D%=;\n"
                 "add.u32 n, n, 1;\nsetp.lt.u32 p, n, 0x1000000;\n@p bra W%=;\ntrap;\nD%=:\n}" ::"r"(bar), "r"(parity) : "memory");
}
__device__ __forceinline__ void watchdog(uint32_t bar) {
    asm volatile("{\n.reg .pred p;\n.reg .u32 n;\nmov.u32 n, 0;\nW%=:\nmbarrier.try_wait.parity.shared::cta.b64 p, [%0], 0, 0x4000;\n@p bra D%=;\n"
                 "add.u32 n, n, 1;\nsetp.lt.u32 p, n, 0x20000;\n@p bra W%=;\ntrap;\nD%=:\n}" ::"r"(bar) : "memory");
}
__device__ __forceinline__ void tma2d(uint32_t dst, const CUtensorMap* tm, int c0, int c1, uint32_t bar) {
    asm volatile("cp.async.bulk.tensor.2d.shared::cluster.global.mbarrier::complete_tx::bytes [%0], [%1, {%3, %4}], [%2];"
                 ::"r"(dst), "l"(tm), "r"(bar), "r"(c0), "r"(c1) : "memory");
}
__device__ __forceinline__ void tma2d_mc(uint32_t dst, const CUtensorMap* tm, int c0, int c1, uint32_t bar) {
    asm volatile("cp.async.bulk.tensor.2d.shared::cluster.global.mbarrier::complete_tx::bytes.multicast::cluster [%0], [%1, {%3, %4}], [%2], %5;"
                 ::"r"(dst), "l"(tm), "r"(bar), "r"(c0), "r"(c1), "h"((uint16_t)3) : "memory");
}
__device__ __forceinline__ void tma2d_store(const CUtensorMap* tm, int c0, int c1, uint32_t src) {
    asm volatile("cp.async.bulk.tensor.2d.global.shared::cta.bulk_group [%0, {%2, %3}], [%1];" ::"l"(tm), "r"(src), "r"(c0), "r"(c1) : "memory");
}
__device__ __forceinline__ void bulk_ld(uint32_t dst, const void* src, uint32_t bytes, uint32_t bar) {
    asm volatile("cp.async.bulk.shared::cluster.global.mbarrier::complete_tx::bytes [%0], [%1], %2, [%3];" ::"r"(dst), "l"(src), "r"(bytes), "r"(bar) : "memory");
}
__device__ __forceinline__ void bulk_ld_mc(uint32_t dst, const void* src, uint32_t bytes, uint32_t bar, uint16_t mask) {
    asm volatile("cp.async.bulk.shared::cluster.global.mbarrier::complete_tx::bytes.multicast::cluster [%0], [%1], %2, [%3], %4;"
                 ::"r"(dst), "l"(src), "r"(bytes), "r"(bar), "h"(mask) : "memory");
}
__device__ __forceinline__ void bulk_st(void* dst, uint32_t src, uint32_t bytes) {
    asm volatile("cp.async.bulk.global.shared::cta.bulk_group [%0], [%1], %2;" ::"l"(dst), "r"(src), "r"(bytes) : "memory");
}
__device__ __forceinline__ void bulk_push(uint32_t dst_cluster, uint32_t src, uint32_t bytes, uint32_t bar_cluster) {
    asm volatile("cp.async.bulk.shared::cluster.shared::cta.mbarrier::complete_tx::bytes [%0], [%1], %2, [%3];" ::"r"(dst_cluster), "r"(src), "r"(bytes), "r"(bar_cluster) : "memory");
}
__device__ __forceinline__ void bulk_commit() { asm volatile("cp.async.bulk.commit_group;" ::: "memory"); }
__device__ __forceinline__ void fence_gpu() { asm volatile("fence.release.gpu;" ::: "memory"); }
__device__ __forceinline__ void bulk_wait_release() { asm volatile("cp.async.bulk.wait_group 0;" ::: "memory"); fence_gpu(); }
__device__ __forceinline__ void l2_prefetch(const void* p, uint32_t bytes) { asm volatile("cp.async.bulk.prefetch.L2.global [%0], %1;" ::"l"(p), "r"(bytes) : "memory"); }
__device__ __forceinline__ void fence_async_smem() { asm volatile("fence.proxy.async.shared::cta;" ::: "memory"); }
__device__ __forceinline__ void fence_async_all() { asm volatile("fence.proxy.async.global;" ::: "memory"); }
__device__ __forceinline__ void cluster_arrive_relaxed() { asm volatile("barrier.cluster.arrive.relaxed.aligned;" ::: "memory"); }
__device__ __forceinline__ void cluster_wait() { asm volatile("barrier.cluster.wait.acquire.aligned;" ::: "memory"); }
__device__ __forceinline__ void bar_sync(int id, int n) { asm volatile("bar.sync %0, %1;" ::"r"(id), "r"(n) : "memory"); }
__device__ __forceinline__ void wg_fence() { asm volatile("wgmma.fence.sync.aligned;" ::: "memory"); }
__device__ __forceinline__ void wg_commit() { asm volatile("wgmma.commit_group.sync.aligned;" ::: "memory"); }
template <int N> __device__ __forceinline__ void wg_wait() { asm volatile("wgmma.wait_group.sync.aligned %0;" ::"n"(N) : "memory"); }
template <int N> __device__ __forceinline__ void pin(float (&a)[N]) {
#pragma unroll
    for (int i = 0; i < N; i++) asm volatile("" : "+f"(a[i])::"memory");
}
template <int N> __device__ __forceinline__ void pin(uint32_t (&a)[N]) {
#pragma unroll
    for (int i = 0; i < N; i++) asm volatile("" : "+r"(a[i])::"memory");
}
__device__ __forceinline__ void pin4(uint32_t& a, uint32_t& b, uint32_t& c, uint32_t& d) { asm volatile("" : "+r"(a), "+r"(b), "+r"(c), "+r"(d)::"memory"); }
constexpr uint32_t H_SW = (1024 >> 4) | (1u << 30);
constexpr uint32_t H_CK = (128 >> 4);
constexpr uint32_t H_CM = (1024 >> 4);
constexpr uint32_t H_CW = (1792 >> 4);
__device__ __forceinline__ uint32_t dlo(uint32_t addr, uint32_t lbo) { return ((addr & 0x3FFFF) >> 4) | ((lbo >> 4) << 16); }
__device__ __forceinline__ void ldsm4(uint32_t addr, uint32_t& a, uint32_t& b, uint32_t& c, uint32_t& d) {
    asm volatile("ldmatrix.sync.aligned.m8n8.x4.shared.b16 {%0,%1,%2,%3}, [%4];" : "=r"(a), "=r"(b), "=r"(c), "=r"(d) : "r"(addr) : "memory");
}
__device__ __forceinline__ void stsm4(uint32_t addr, uint32_t a, uint32_t b, uint32_t c, uint32_t d) {
    asm volatile("stmatrix.sync.aligned.m8n8.x4.shared.b16 [%0], {%1,%2,%3,%4};" ::"r"(addr), "r"(a), "r"(b), "r"(c), "r"(d) : "memory");
}
__device__ __forceinline__ void stsm2(uint32_t addr, uint32_t a, uint32_t b) {
    asm volatile("stmatrix.sync.aligned.m8n8.x2.shared.b16 [%0], {%1,%2};" ::"r"(addr), "r"(a), "r"(b) : "memory");
}
__device__ __forceinline__ uint4 lds128(uint32_t addr) { uint4 v; asm volatile("ld.shared.v4.u32 {%0,%1,%2,%3}, [%4];" : "=r"(v.x), "=r"(v.y), "=r"(v.z), "=r"(v.w) : "r"(addr) : "memory"); return v; }
__device__ __forceinline__ float2 lds64f(uint32_t addr) { float2 v; asm volatile("ld.shared.v2.f32 {%0,%1}, [%2];" : "=f"(v.x), "=f"(v.y) : "r"(addr) : "memory"); return v; }
__device__ __forceinline__ float lds32f(uint32_t addr) { float v; asm volatile("ld.shared.f32 %0, [%1];" : "=f"(v) : "r"(addr) : "memory"); return v; }
__device__ __forceinline__ void sts32(uint32_t addr, uint32_t v) { asm volatile("st.shared.u32 [%0], %1;" ::"r"(addr), "r"(v) : "memory"); }
__device__ __forceinline__ void sts64(uint32_t addr, uint32_t a, uint32_t b) { asm volatile("st.shared.v2.u32 [%0], {%1,%2};" ::"r"(addr), "r"(a), "r"(b) : "memory"); }
__device__ __forceinline__ uint32_t ld_rlx(const void* p) { uint32_t v; asm volatile("ld.relaxed.gpu.global.u32 %0, [%1];" : "=r"(v) : "l"(p) : "memory"); return v; }
__device__ __forceinline__ uint2 ld_rlx2(const void* p) { uint2 v; asm volatile("ld.relaxed.gpu.global.v2.u32 {%0,%1}, [%2];" : "=r"(v.x), "=r"(v.y) : "l"(p) : "memory"); return v; }
__device__ __forceinline__ uint4 ld_rlx4(const void* p) { uint4 v; asm volatile("ld.relaxed.gpu.global.v4.u32 {%0,%1,%2,%3}, [%4];" : "=r"(v.x), "=r"(v.y), "=r"(v.z), "=r"(v.w) : "l"(p) : "memory"); return v; }
__device__ __forceinline__ void st_rlx(void* p, uint32_t v) { asm volatile("st.relaxed.gpu.global.u32 [%0], %1;" ::"l"(p), "r"(v) : "memory"); }
__device__ __forceinline__ void st_rlx2(void* p, uint32_t a, uint32_t b) { asm volatile("st.relaxed.gpu.global.v2.u32 [%0], {%1,%2};" ::"l"(p), "r"(a), "r"(b) : "memory"); }
__device__ __forceinline__ void st_rlx4(void* p, uint32_t a, uint32_t b, uint32_t c, uint32_t d) { asm volatile("st.relaxed.gpu.global.v4.u32 [%0], {%1,%2,%3,%4};" ::"l"(p), "r"(a), "r"(b), "r"(c), "r"(d) : "memory"); }
__device__ __forceinline__ uint32_t pack_bf16(float lo, float hi) { uint32_t r; asm("cvt.rn.bf16x2.f32 %0, %1, %2;" : "=r"(r) : "f"(hi), "f"(lo)); return r; }
__device__ __forceinline__ float bf_lo(uint32_t v) { return __uint_as_float(v << 16); }
__device__ __forceinline__ float bf_hi(uint32_t v) { return __uint_as_float(v & 0xffff0000u); }
__device__ __forceinline__ float bf_round(float x) { return __bfloat162float(__float2bfloat16_rn(x)); }
__device__ __forceinline__ uint32_t fma_bf16x2(uint32_t a, uint32_t b, uint32_t c) { uint32_t r; asm("fma.rn.bf16x2 %0, %1, %2, %3;" : "=r"(r) : "r"(a), "r"(b), "r"(c)); return r; }
__device__ __forceinline__ float ex2(float x) { float r; asm("ex2.approx.ftz.f32 %0, %1;" : "=f"(r) : "f"(x)); return r; }
__device__ __forceinline__ float tanh_fast(float x) { float r; asm("tanh.approx.f32 %0, %1;" : "=f"(r) : "f"(x)); return r; }
__device__ __forceinline__ float gelu_half(float h) {
    const float u = h * fmaf(h * h, 8.0f * 0.7978845608028654f * 0.044715f, 2.0f * 0.7978845608028654f);
    return fmaf(h, tanh_fast(u), h);
}
__device__ __forceinline__ uint32_t* flag_ptr(int kind, int cta) { return &g_flag[(kind * 128 + cta) * 8]; }
__device__ __forceinline__ void poll_flag(const uint32_t* f, uint32_t tag) {
    while (ld_rlx(f) != tag) __nanosleep(POLL_NS);
}
struct LnRow { uint32_t rh, rl, nm; };
__device__ __forceinline__ LnRow ln_row(float mean, float var) {
    const float r = rsqrtf(var + 1e-5f), rh = bf_round(r);
    LnRow o;
    o.rh = pack_bf16(rh, rh); o.rl = pack_bf16(r - rh, r - rh); o.nm = pack_bf16(-mean * r, -mean * r);
    return o;
}
__device__ __forceinline__ uint32_t ln_norm(uint32_t x2, const LnRow& k) { return fma_bf16x2(x2, k.rh, fma_bf16x2(x2, k.rl, k.nm)); }
__device__ __forceinline__ void chan_merge(float& m, float& q, float m2, float q2, float n) {
    float d = m - m2;
    q = q + q2 + d * d * (0.5f * n);
    m = 0.5f * (m + m2);
}

template <uint32_t HA, uint32_t HB, int TB> __device__ __forceinline__ void wgmma_ss_n16(float (&d)[8], uint32_t da, uint32_t db, int sd) {
    asm volatile("{\n.reg .pred p;\n.reg .b64 da, db;\nsetp.ne.b32 p, %10, 0;\nmov.b64 da, {%8, %12};\nmov.b64 db, {%9, %13};\n"
                 "wgmma.mma_async.sync.aligned.m64n16k16.f32.bf16.bf16 {%0, %1, %2, %3, %4, %5, %6, %7}, da, db, p, 1, 1, 0, %11;\n}"
                 : "+f"(d[0]), "+f"(d[1]), "+f"(d[2]), "+f"(d[3]), "+f"(d[4]), "+f"(d[5]), "+f"(d[6]), "+f"(d[7])
                 : "r"(da), "r"(db), "r"(sd), "n"(TB), "n"(HA), "n"(HB));
}
template <uint32_t HA, uint32_t HB, int TB> __device__ __forceinline__ void wgmma_ss_n32(float (&d)[16], uint32_t da, uint32_t db, int sd) {
    asm volatile("{\n.reg .pred p;\n.reg .b64 da, db;\nsetp.ne.b32 p, %18, 0;\nmov.b64 da, {%16, %20};\nmov.b64 db, {%17, %21};\n"
                 "wgmma.mma_async.sync.aligned.m64n32k16.f32.bf16.bf16 {%0, %1, %2, %3, %4, %5, %6, %7, %8, %9, %10, %11, %12, %13, %14, %15}, da, db, p, 1, 1, 0, %19;\n}"
                 : "+f"(d[0]), "+f"(d[1]), "+f"(d[2]), "+f"(d[3]), "+f"(d[4]), "+f"(d[5]), "+f"(d[6]), "+f"(d[7]), "+f"(d[8]), "+f"(d[9]), "+f"(d[10]), "+f"(d[11]), "+f"(d[12]), "+f"(d[13]), "+f"(d[14]), "+f"(d[15])
                 : "r"(da), "r"(db), "r"(sd), "n"(TB), "n"(HA), "n"(HB));
}
template <uint32_t HA, uint32_t HB, int TB> __device__ __forceinline__ void wgmma_ss_n56(float (&d)[28], uint32_t da, uint32_t db, int sd) {
    asm volatile("{\n.reg .pred p;\n.reg .b64 da, db;\nsetp.ne.b32 p, %30, 0;\nmov.b64 da, {%28, %32};\nmov.b64 db, {%29, %33};\n"
                 "wgmma.mma_async.sync.aligned.m64n56k16.f32.bf16.bf16 {%0, %1, %2, %3, %4, %5, %6, %7, %8, %9, %10, %11, %12, %13, %14, %15, %16, %17, %18, %19, %20, %21, %22, %23, %24, %25, %26, %27}, da, db, p, 1, 1, 0, %31;\n}"
                 : "+f"(d[0]), "+f"(d[1]), "+f"(d[2]), "+f"(d[3]), "+f"(d[4]), "+f"(d[5]), "+f"(d[6]), "+f"(d[7]), "+f"(d[8]), "+f"(d[9]), "+f"(d[10]), "+f"(d[11]), "+f"(d[12]), "+f"(d[13]), "+f"(d[14]), "+f"(d[15]), "+f"(d[16]), "+f"(d[17]), "+f"(d[18]), "+f"(d[19]), "+f"(d[20]), "+f"(d[21]), "+f"(d[22]), "+f"(d[23]), "+f"(d[24]), "+f"(d[25]), "+f"(d[26]), "+f"(d[27])
                 : "r"(da), "r"(db), "r"(sd), "n"(TB), "n"(HA), "n"(HB));
}
template <uint32_t HA, uint32_t HB, int TB> __device__ __forceinline__ void wgmma_ss_n112(float (&d)[56], uint32_t da, uint32_t db, int sd) {
    asm volatile("{\n.reg .pred p;\n.reg .b64 da, db;\nsetp.ne.b32 p, %58, 0;\nmov.b64 da, {%56, %60};\nmov.b64 db, {%57, %61};\n"
                 "wgmma.mma_async.sync.aligned.m64n112k16.f32.bf16.bf16 {%0, %1, %2, %3, %4, %5, %6, %7, %8, %9, %10, %11, %12, %13, %14, %15, %16, %17, %18, %19, %20, %21, %22, %23, %24, %25, %26, %27, %28, %29, %30, %31, %32, %33, %34, %35, %36, %37, %38, %39, %40, %41, %42, %43, %44, %45, %46, %47, %48, %49, %50, %51, %52, %53, %54, %55}, da, db, p, 1, 1, 0, %59;\n}"
                 : "+f"(d[0]), "+f"(d[1]), "+f"(d[2]), "+f"(d[3]), "+f"(d[4]), "+f"(d[5]), "+f"(d[6]), "+f"(d[7]), "+f"(d[8]), "+f"(d[9]), "+f"(d[10]), "+f"(d[11]), "+f"(d[12]), "+f"(d[13]), "+f"(d[14]), "+f"(d[15]), "+f"(d[16]), "+f"(d[17]), "+f"(d[18]), "+f"(d[19]), "+f"(d[20]), "+f"(d[21]), "+f"(d[22]), "+f"(d[23]), "+f"(d[24]), "+f"(d[25]), "+f"(d[26]), "+f"(d[27]), "+f"(d[28]), "+f"(d[29]), "+f"(d[30]), "+f"(d[31]), "+f"(d[32]), "+f"(d[33]), "+f"(d[34]), "+f"(d[35]), "+f"(d[36]), "+f"(d[37]), "+f"(d[38]), "+f"(d[39]), "+f"(d[40]), "+f"(d[41]), "+f"(d[42]), "+f"(d[43]), "+f"(d[44]), "+f"(d[45]), "+f"(d[46]), "+f"(d[47]), "+f"(d[48]), "+f"(d[49]), "+f"(d[50]), "+f"(d[51]), "+f"(d[52]), "+f"(d[53]), "+f"(d[54]), "+f"(d[55])
                 : "r"(da), "r"(db), "r"(sd), "n"(TB), "n"(HA), "n"(HB));
}
template <uint32_t HB, int TB> __device__ __forceinline__ void wgmma_rs_n32(float (&d)[16], uint32_t a0, uint32_t a1, uint32_t a2, uint32_t a3, uint32_t db, int sd) {
    asm volatile("{\n.reg .pred p;\n.reg .b64 db;\nsetp.ne.b32 p, %21, 0;\nmov.b64 db, {%20, %23};\n"
                 "wgmma.mma_async.sync.aligned.m64n32k16.f32.bf16.bf16 {%0, %1, %2, %3, %4, %5, %6, %7, %8, %9, %10, %11, %12, %13, %14, %15}, {%16, %17, %18, %19}, db, p, 1, 1, %22;\n}"
                 : "+f"(d[0]), "+f"(d[1]), "+f"(d[2]), "+f"(d[3]), "+f"(d[4]), "+f"(d[5]), "+f"(d[6]), "+f"(d[7]), "+f"(d[8]), "+f"(d[9]), "+f"(d[10]), "+f"(d[11]), "+f"(d[12]), "+f"(d[13]), "+f"(d[14]), "+f"(d[15])
                 : "r"(a0), "r"(a1), "r"(a2), "r"(a3), "r"(db), "r"(sd), "n"(TB), "n"(HB));
}
template <uint32_t HB, int TB> __device__ __forceinline__ void wgmma_rs_n56(float (&d)[28], uint32_t a0, uint32_t a1, uint32_t a2, uint32_t a3, uint32_t db, int sd) {
    asm volatile("{\n.reg .pred p;\n.reg .b64 db;\nsetp.ne.b32 p, %33, 0;\nmov.b64 db, {%32, %35};\n"
                 "wgmma.mma_async.sync.aligned.m64n56k16.f32.bf16.bf16 {%0, %1, %2, %3, %4, %5, %6, %7, %8, %9, %10, %11, %12, %13, %14, %15, %16, %17, %18, %19, %20, %21, %22, %23, %24, %25, %26, %27}, {%28, %29, %30, %31}, db, p, 1, 1, %34;\n}"
                 : "+f"(d[0]), "+f"(d[1]), "+f"(d[2]), "+f"(d[3]), "+f"(d[4]), "+f"(d[5]), "+f"(d[6]), "+f"(d[7]), "+f"(d[8]), "+f"(d[9]), "+f"(d[10]), "+f"(d[11]), "+f"(d[12]), "+f"(d[13]), "+f"(d[14]), "+f"(d[15]), "+f"(d[16]), "+f"(d[17]), "+f"(d[18]), "+f"(d[19]), "+f"(d[20]), "+f"(d[21]), "+f"(d[22]), "+f"(d[23]), "+f"(d[24]), "+f"(d[25]), "+f"(d[26]), "+f"(d[27])
                 : "r"(a0), "r"(a1), "r"(a2), "r"(a3), "r"(db), "r"(sd), "n"(TB), "n"(HB));
}
template <uint32_t HB, int TB> __device__ __forceinline__ void wgmma_rs_n64(float (&d)[32], uint32_t a0, uint32_t a1, uint32_t a2, uint32_t a3, uint32_t db, int sd) {
    asm volatile("{\n.reg .pred p;\n.reg .b64 db;\nsetp.ne.b32 p, %37, 0;\nmov.b64 db, {%36, %39};\n"
                 "wgmma.mma_async.sync.aligned.m64n64k16.f32.bf16.bf16 {%0, %1, %2, %3, %4, %5, %6, %7, %8, %9, %10, %11, %12, %13, %14, %15, %16, %17, %18, %19, %20, %21, %22, %23, %24, %25, %26, %27, %28, %29, %30, %31}, {%32, %33, %34, %35}, db, p, 1, 1, %38;\n}"
                 : "+f"(d[0]), "+f"(d[1]), "+f"(d[2]), "+f"(d[3]), "+f"(d[4]), "+f"(d[5]), "+f"(d[6]), "+f"(d[7]), "+f"(d[8]), "+f"(d[9]), "+f"(d[10]), "+f"(d[11]), "+f"(d[12]), "+f"(d[13]), "+f"(d[14]), "+f"(d[15]), "+f"(d[16]), "+f"(d[17]), "+f"(d[18]), "+f"(d[19]), "+f"(d[20]), "+f"(d[21]), "+f"(d[22]), "+f"(d[23]), "+f"(d[24]), "+f"(d[25]), "+f"(d[26]), "+f"(d[27]), "+f"(d[28]), "+f"(d[29]), "+f"(d[30]), "+f"(d[31])
                 : "r"(a0), "r"(a1), "r"(a2), "r"(a3), "r"(db), "r"(sd), "n"(TB), "n"(HB));
}
template <uint32_t HB, int TB> __device__ __forceinline__ void wgmma_rs_n112(float (&d)[56], uint32_t a0, uint32_t a1, uint32_t a2, uint32_t a3, uint32_t db, int sd) {
    asm volatile("{\n.reg .pred p;\n.reg .b64 db;\nsetp.ne.b32 p, %61, 0;\nmov.b64 db, {%60, %63};\n"
                 "wgmma.mma_async.sync.aligned.m64n112k16.f32.bf16.bf16 {%0, %1, %2, %3, %4, %5, %6, %7, %8, %9, %10, %11, %12, %13, %14, %15, %16, %17, %18, %19, %20, %21, %22, %23, %24, %25, %26, %27, %28, %29, %30, %31, %32, %33, %34, %35, %36, %37, %38, %39, %40, %41, %42, %43, %44, %45, %46, %47, %48, %49, %50, %51, %52, %53, %54, %55}, {%56, %57, %58, %59}, db, p, 1, 1, %62;\n}"
                 : "+f"(d[0]), "+f"(d[1]), "+f"(d[2]), "+f"(d[3]), "+f"(d[4]), "+f"(d[5]), "+f"(d[6]), "+f"(d[7]), "+f"(d[8]), "+f"(d[9]), "+f"(d[10]), "+f"(d[11]), "+f"(d[12]), "+f"(d[13]), "+f"(d[14]), "+f"(d[15]), "+f"(d[16]), "+f"(d[17]), "+f"(d[18]), "+f"(d[19]), "+f"(d[20]), "+f"(d[21]), "+f"(d[22]), "+f"(d[23]), "+f"(d[24]), "+f"(d[25]), "+f"(d[26]), "+f"(d[27]), "+f"(d[28]), "+f"(d[29]), "+f"(d[30]), "+f"(d[31]), "+f"(d[32]), "+f"(d[33]), "+f"(d[34]), "+f"(d[35]), "+f"(d[36]), "+f"(d[37]), "+f"(d[38]), "+f"(d[39]), "+f"(d[40]), "+f"(d[41]), "+f"(d[42]), "+f"(d[43]), "+f"(d[44]), "+f"(d[45]), "+f"(d[46]), "+f"(d[47]), "+f"(d[48]), "+f"(d[49]), "+f"(d[50]), "+f"(d[51]), "+f"(d[52]), "+f"(d[53]), "+f"(d[54]), "+f"(d[55])
                 : "r"(a0), "r"(a1), "r"(a2), "r"(a3), "r"(db), "r"(sd), "n"(TB), "n"(HB));
}

const unsigned char h_role[68] = {35, 0, 1, 2, 3, 32, 33, 34, 39, 4, 5, 6, 7, 36, 37, 38, 43, 8, 9, 10, 11, 40, 41, 42, 47, 12, 13, 14, 15, 44, 45, 46, 16, 17, 18, 19, 48, 49, 50, 20, 21, 22, 23, 52, 53, 54, 24, 25, 26, 27, 56, 57, 58, 28, 29, 30, 31, 60, 61, 62, 255, 255, 51, 55, 59, 63, 255, 255};

struct Ctx {
    uint32_t sb;
    uint32_t peer_sb;
    uint32_t self_cl;
    int tm, tn, rank, b;
    int jb;
};
__device__ __forceinline__ uint32_t uni_(uint32_t v) { return __shfl_sync(0xffffffffu, v, 0); }
__device__ __forceinline__ uint32_t BAR(const Ctx& c, int i) { return c.sb + MISC + 8 * i; }
__device__ __forceinline__ uint32_t get_tag(const Ctx& c) {
    mbar_wait(BAR(c, B_TAG), 0);
    uint32_t v;
    asm volatile("ld.shared.u32 %0, [%1];" : "=r"(v) : "r"(c.sb + TAGW) : "memory");
    return v;
}
__device__ __forceinline__ uint32_t fixed_role(const Params& p, const Ctx& c, uint32_t& key) {
    uint32_t smid, peer;
    mbar_wait(BAR(c, B_SMID), 0);
    asm volatile("mov.u32 %0, %%smid;" : "=r"(smid));
    asm volatile("ld.shared.u32 %0, [%1];" : "=r"(peer) : "r"(c.sb + TAGW + 8) : "memory");
    key = 256u + (c.rank ? peer : smid);
    return ((peer ^ smid) == 1u && (smid & 1u) == (uint32_t)c.rank && smid < SMID_MAX) ? p.role[smid >> 1] : 255u;
}
__device__ __forceinline__ void resolve_role(const Params& p, Ctx& c) {
    uint32_t key, r = fixed_role(p, c, key);
    if (__builtin_expect(r == 255u, 0)) {
        mbar_wait(BAR(c, B_ROLE), 0);
        asm volatile("ld.shared.u32 %0, [%1];" : "=r"(r) : "r"(c.sb + TAGW + 12) : "memory");
    }
    r = uni_(r);
    c.b = r * 2 + c.rank; c.tm = c.b >> 3; c.tn = c.b & 7;
}
__device__ __forceinline__ void arrive_both(const Ctx& c, int i, int lane) {
    if (lane < 2) mbar_arrive_cl((lane == 0 ? c.self_cl : c.peer_sb) + MISC + 8 * i);
}
__device__ __forceinline__ uint32_t uni(uint32_t v) { return __shfl_sync(0xffffffffu, v, 0); }
__device__ __forceinline__ bool elect() {
    uint32_t r;
    asm volatile("{\n.reg .pred p;\nelect.sync _|p, 0xffffffff;\nselp.u32 %0, 1, 0, p;\n}" : "=r"(r));
    return r;
}

__device__ __noinline__ float4 gather_stats(const uint4* p, uint32_t tag, float n) {
    uint4 a0, b0, a1, b1;
    while (true) {
        a0 = ld_rlx4(p); b0 = ld_rlx4(p + 64); a1 = ld_rlx4(p + 8); b1 = ld_rlx4(p + 72);
        bool ok = a0.y == tag && a0.w == tag && b0.y == tag && b0.w == tag && a1.y == tag && a1.w == tag && b1.y == tag && b1.w == tag;
        if (__all_sync(0xffffffffu, ok)) break;
        __nanosleep(GATHER_NS);
    }
    float m0 = __uint_as_float(a0.x), q0 = __uint_as_float(a0.z), m1 = __uint_as_float(a1.x), q1 = __uint_as_float(a1.z);
    chan_merge(m0, q0, __uint_as_float(b0.x), __uint_as_float(b0.z), n);
    chan_merge(m1, q1, __uint_as_float(b1.x), __uint_as_float(b1.z), n);
#pragma unroll
    for (int s = 1; s <= 2; s <<= 1) {
        float mo0 = __shfl_xor_sync(0xffffffffu, m0, s), qo0 = __shfl_xor_sync(0xffffffffu, q0, s);
        float mo1 = __shfl_xor_sync(0xffffffffu, m1, s), qo1 = __shfl_xor_sync(0xffffffffu, q1, s);
        chan_merge(m0, q0, mo0, qo0, n * 2 * s);
        chan_merge(m1, q1, mo1, qo1, n * 2 * s);
    }
    const float inv = __fdividef(0.125f, n);
    return make_float4(m0, q0 * inv, m1, q1 * inv);
}
struct F28 { float v[28]; };
struct U14 { uint32_t v[14]; };
__device__ __noinline__ float4 stats7(U14 x) {
    float s0 = 0.f, s1 = 0.f;
#pragma unroll
    for (int j = 0; j < 7; j++) { s0 += bf_lo(x.v[2 * j]) + bf_hi(x.v[2 * j]); s1 += bf_lo(x.v[2 * j + 1]) + bf_hi(x.v[2 * j + 1]); }
    s0 += __shfl_xor_sync(0xffffffffu, s0, 1); s1 += __shfl_xor_sync(0xffffffffu, s1, 1);
    s0 += __shfl_xor_sync(0xffffffffu, s0, 2); s1 += __shfl_xor_sync(0xffffffffu, s1, 2);
    const float m0 = s0 * (1.0f / 56), m1 = s1 * (1.0f / 56);
    float q0 = 0.f, q1 = 0.f;
#pragma unroll
    for (int j = 0; j < 7; j++) {
        float a = bf_lo(x.v[2 * j]) - m0, b = bf_hi(x.v[2 * j]) - m0, c = bf_lo(x.v[2 * j + 1]) - m1, d = bf_hi(x.v[2 * j + 1]) - m1;
        q0 = fmaf(a, a, q0); q0 = fmaf(b, b, q0); q1 = fmaf(c, c, q1); q1 = fmaf(d, d, q1);
    }
    q0 += __shfl_xor_sync(0xffffffffu, q0, 1); q1 += __shfl_xor_sync(0xffffffffu, q1, 1);
    q0 += __shfl_xor_sync(0xffffffffu, q0, 2); q1 += __shfl_xor_sync(0xffffffffu, q1, 2);
    return make_float4(m0, q0, m1, q1);
}
template <int O, int N> __device__ __forceinline__ float4 stats_of(const uint32_t (&v)[N]) {
    U14 x;
#pragma unroll
    for (int i = 0; i < 14; i++) x.v[i] = v[O + i];
    return stats7(x);
}
__device__ __forceinline__ void publish_stats(const float4& s, uint4* dst, int t, uint32_t tag) {
    if (t < 2) st_rlx4(dst, __float_as_uint(t ? s.z : s.x), tag, __float_as_uint(t ? s.w : s.y), tag);
}
__device__ __noinline__ U14 resid7(F28 a, U14 x, uint32_t gate) {
#pragma unroll
    for (int j = 0; j < 7; j++) {
        const float2 gt = lds64f(gate + j * 32);
        x.v[2 * j] = pack_bf16(fmaf(gt.x, a.v[4 * j], bf_lo(x.v[2 * j])), fmaf(gt.y, a.v[4 * j + 1], bf_hi(x.v[2 * j])));
        x.v[2 * j + 1] = pack_bf16(fmaf(gt.x, a.v[4 * j + 2], bf_lo(x.v[2 * j + 1])), fmaf(gt.y, a.v[4 * j + 3], bf_hi(x.v[2 * j + 1])));
    }
    return x;
}
__device__ __forceinline__ void resid(uint32_t (&x)[14], const float (&ac)[28], uint32_t gate) {
    F28 a; U14 u;
#pragma unroll
    for (int i = 0; i < 28; i++) a.v[i] = ac[i];
#pragma unroll
    for (int i = 0; i < 14; i++) u.v[i] = x[i];
    u = resid7(a, u, gate);
#pragma unroll
    for (int i = 0; i < 14; i++) x[i] = u.v[i];
}
template <int NB, int CS = 1024>
__device__ __forceinline__ void store_cm8(uint32_t lane_addr, const uint32_t (&v)[2 * NB]) {
#pragma unroll
    for (int j = 0; j + 1 < NB; j += 2) stsm4(lane_addr + j * CS, v[2 * j], v[2 * j + 1], v[2 * j + 2], v[2 * j + 3]);
    if (NB & 1) stsm2(lane_addr + (NB - 1) * CS, v[2 * NB - 2], v[2 * NB - 1]);
}
template <int NB, int CS = 1024>
__device__ __forceinline__ void store_cm8_g(unsigned char* lane_ptr, const uint32_t (&v)[2 * NB]) {
    uint32_t* p = reinterpret_cast<uint32_t*>(lane_ptr);
#pragma unroll
    for (int j = 0; j < NB; j++) { p[j * (CS / 4)] = v[2 * j]; p[j * (CS / 4) + 32] = v[2 * j + 1]; }
}
__device__ __forceinline__ void signal_global(const Ctx& c, int bar, int lane) {
    __syncwarp();
    if (lane == 0) mbar_arrive(BAR(c, bar));
}
__device__ __forceinline__ void signal_store(const Ctx& c, int bar, int lane) {
    fence_async_smem();
    __syncwarp();
    if (lane == 0) mbar_arrive(BAR(c, bar));
}

constexpr float SM_C = 0.18898223650461362f * 1.4426950408889634f;
__device__ __forceinline__ void cross_mask(float (&s)[32], bool dg, int ws, bool k0, bool k1) {
    const float NEG = -INFINITY;
    const bool c0 = k0 == dg, c1 = k1 == dg;
#pragma unroll
    for (int r = 0; r < 4; r++) {
        if (r == ws) {
            s[8 * r] = c0 ? s[8 * r] : NEG; s[8 * r + 1] = c1 ? s[8 * r + 1] : NEG;
            s[8 * r + 2] = dg ? s[8 * r + 2] : NEG; s[8 * r + 3] = dg ? s[8 * r + 3] : NEG;
            s[8 * r + 4] = dg ? NEG : s[8 * r + 4]; s[8 * r + 5] = dg ? NEG : s[8 * r + 5];
            s[8 * r + 6] = c0 ? s[8 * r + 6] : NEG; s[8 * r + 7] = c1 ? s[8 * r + 7] : NEG;
        }
    }
}
__device__ __forceinline__ void fill_off(float (&s)[32], uint32_t on, float f0, float f1) {
#pragma unroll
    for (int r = 0; r < 4; r++) {
        if (!(on & (1u << r))) {
            s[8 * r] = f0; s[8 * r + 1] = f0; s[8 * r + 4] = f0; s[8 * r + 5] = f0;
            s[8 * r + 2] = f1; s[8 * r + 3] = f1; s[8 * r + 6] = f1; s[8 * r + 7] = f1;
        }
    }
}
__device__ __forceinline__ void quad_max(float& x0, float& x1) {
    x0 = fmaxf(x0, __shfl_xor_sync(0xffffffffu, x0, 1)); x1 = fmaxf(x1, __shfl_xor_sync(0xffffffffu, x1, 1));
    x0 = fmaxf(x0, __shfl_xor_sync(0xffffffffu, x0, 2)); x1 = fmaxf(x1, __shfl_xor_sync(0xffffffffu, x1, 2));
}
__device__ __forceinline__ void pex2(float& x, uint32_t on) { asm("{\n.reg .pred p;\nsetp.ne.u32 p, %1, 0;\n@p ex2.approx.ftz.f32 %0, %0;\n}" : "+f"(x) : "r"(on)); }
__device__ __forceinline__ void exp_block(const float (&s)[32], uint32_t (&p)[16], uint32_t on, float m0, float m1, uint32_t scratch) {
    uint32_t chk = 0;
#pragma unroll
    for (int i = 0; i < 16; i++) {
        const float m = (i & 1) ? m1 : m0;
        float x = s[2 * i] - m, y = s[2 * i + 1] - m;
        pex2(x, on & (1u << (i >> 2))); pex2(y, on & (1u << (i >> 2)));
        p[i] = pack_bf16(x, y);
        chk ^= p[i];
    }
    sts32(scratch, chk);
}
__device__ __forceinline__ void issue_qk(float (&s)[32], const uint32_t (&q)[8], uint32_t dk) {
    wgmma_rs_n64<H_CK, 0>(s, q[0], q[1], q[2], q[3], dk, 0);
    wgmma_rs_n64<H_CK, 0>(s, q[4], q[5], q[6], q[7], dk + 128, 1);
}
__device__ __forceinline__ void issue_pv(float (&o)[16], const uint32_t (&p)[16], uint32_t dv, int acc) {
#pragma unroll
    for (int ks = 0; ks < 4; ks++) wgmma_rs_n32<H_CM, 1>(o, p[4 * ks], p[4 * ks + 1], p[4 * ks + 2], p[4 * ks + 3], dv + ks * 16, ks == 0 ? acc : 1);
}
struct G7 { uint32_t v[14]; float s0, q0, s1, q1; };
__device__ __noinline__ G7 gelu7(F28 a, uint32_t uv, float r0, float nm0, float r1, float nm1) {
    G7 z;
    z.s0 = z.q0 = z.s1 = z.q1 = 0.f;
#pragma unroll
    for (int j = 0; j < 7; j++) {
        const uint4 w = lds128(uv + j * 64);
        const float u0 = __uint_as_float(w.x), u1 = __uint_as_float(w.y), v0 = __uint_as_float(w.z), v1 = __uint_as_float(w.w);
        const float a0 = gelu_half(fmaf(r0, a.v[4 * j], fmaf(nm0, u0, v0))), a1 = gelu_half(fmaf(r0, a.v[4 * j + 1], fmaf(nm0, u1, v1)));
        const float b0 = gelu_half(fmaf(r1, a.v[4 * j + 2], fmaf(nm1, u0, v0))), b1 = gelu_half(fmaf(r1, a.v[4 * j + 3], fmaf(nm1, u1, v1)));
        z.v[2 * j] = pack_bf16(a0, a1); z.v[2 * j + 1] = pack_bf16(b0, b1);
        z.s0 += a0 + a1; z.q0 = fmaf(a0, a0, fmaf(a1, a1, z.q0));
        z.s1 += b0 + b1; z.q1 = fmaf(b0, b0, fmaf(b1, b1, z.q1));
    }
    return z;
}
template <int J0>
__device__ __forceinline__ void gelu_blocks(uint32_t (&z)[28], float4& st, const float (&ac)[56], uint32_t uv, float r0, float nm0, float r1, float nm1) {
    F28 a;
#pragma unroll
    for (int i = 0; i < 28; i++) a.v[i] = ac[4 * J0 + i];
    const G7 o = gelu7(a, uv + J0 * 64, r0, nm0, r1, nm1);
#pragma unroll
    for (int i = 0; i < 14; i++) z[2 * J0 + i] = o.v[i];
    st.x += o.s0; st.y += o.q0; st.z += o.s1; st.w += o.q1;
}

__device__ __forceinline__ void consumer(const Params& p, Ctx& c) {
    int tid = threadIdx.x;
    asm volatile("mov.u32 %0, %0;" : "+r"(tid));
    const int warp = uni(tid >> 5), wg = warp >> 2, wq = warp & 3, lane = tid & 31, g = lane >> 2, t = lane & 3;
    const int tw = tid & 127;
    const uint32_t sb = c.sb;
    uint2* const modp = &g_modp[(c.jb & 1) * 2688 + (c.jb >> 1) * 32 + 2 * t];
    uint2* const modq = &g_modp[896 + c.jb * 16 + 2 * t];
    if (tid < 4) {
        if (c.jb < 56) {
#pragma unroll
            for (int j = 0; j < 4; j++) st_rlx4(modp + 8 * j, 0, 0, 0, 0);
        }
        if (c.jb < 112) { st_rlx4(modq, 0, 0, 0, 0); st_rlx4(modq + 8, 0, 0, 0, 0); }
    }
    cluster_wait();
    resolve_role(p, c);
    const int tm = c.tm, tn = c.tn, rb = 2 * tm + wg, myu = tn >> 1;
    const uint32_t cm_lane = (uint32_t)((lane >> 4) * 1024 + (2 * wq + ((lane >> 3) & 1)) * 128 + (lane & 7) * 16);
    const int ws = wg ? 3 - wq : wq;
    const uint32_t cm_lane_a = (uint32_t)((lane >> 4) * 1024 + (2 * ws + ((lane >> 3) & 1)) * 128 + (lane & 7) * 16);
    const uint32_t cm2 = wg * 1024 + (lane >> 4) * 1024;
    const uint32_t g_lane = wq * 256 + lane * 4, g_lane_a = ws * 256 + lane * 4, gblk = rb * 8 + tn;
    const int row0 = tm * 128 + wg * 64 + wq * 16 + g;
    const int st_pub = (rb * 8 + tn) * 64 + wq * 16 + g + 8 * t, st_get = (rb * 8 + 2 * t) * 64 + wq * 16 + g;
    if (t < 2) {
#pragma unroll
        for (int k = 0; k < 3; k++) st_rlx4(&g_st[k][st_pub], 0, 0, 0, 0);
    }
    const uint32_t tag = get_tag(c);
    auto silu_vec = [&](uint32_t cv, uint32_t parity) {
        mbar_wait(BAR(c, B_C), parity);
        if (tid < 112) {
            uint32_t c0, c1;
            asm volatile("ld.shared.v2.u32 {%0,%1}, [%2];" : "=r"(c0), "=r"(c1) : "r"(cv + tid * 8) : "memory");
            auto silu = [](float v) { return __fdividef(v, 1.0f + __expf(-v)); };
            sts64(cv + tid * 8, pack_bf16(silu(bf_lo(c0)), silu(bf_hi(c0))), pack_bf16(silu(bf_lo(c1)), silu(bf_hi(c1))));
        }
        fence_async_smem();
        bar_sync(2, 128);
        mbar_wait(BAR(c, B_WM), parity);
    };
    if (c.jb < 56 && wg == 0) {
        silu_vec(sb + WM_BASE + 14336, 0);
        float am[16];
        const uint32_t dA = dlo(sb + WM_BASE + 14336 + (c.jb & 1) * 448, 16), dB = dlo(sb + WM_BASE, 16);
#pragma unroll 1
        for (int i = 0; i < 14; i += 2) {
            wg_fence();
            wgmma_ss_n32<0u, (512u >> 4) | (2u << 30), 1>(am, dA + i * 2, dB + i * 64, i != 0);
            wgmma_ss_n32<0u, (512u >> 4) | (2u << 30), 1>(am, dA + i * 2 + 2, dB + i * 64 + 64, 1);
            wg_commit();
        }
        wg_wait<0>();
        pin(am);
        if (tid < 4) {
#pragma unroll
            for (int j = 0; j < 4; j++) st_rlx4(modp + 8 * j, __float_as_uint(am[4 * j]), tag, __float_as_uint(am[4 * j + 1]), tag);
        }
    }
    if (tid == 0) mbar_arrive(BAR(c, B_WMFREE));
    uint32_t x1p[14];
    auto load_xslice = [&]() {
        const uint32_t xr = sb + R0 + wg * 57344 + (uint32_t)(wq * 16 + (lane & 7) + ((lane >> 3) & 1) * 8) * 128;
        const int cc = 7 * tn + (lane >> 4);
#pragma unroll
        for (int j = 0; j < 6; j += 2) ldsm4(xr + ((cc + j) >> 3) * 8192 + ((((cc + j) & 7) ^ (lane & 7)) << 4), x1p[2 * j], x1p[2 * j + 1], x1p[2 * j + 2], x1p[2 * j + 3]);
        uint32_t d0, d1;
        ldsm4(xr + ((cc + 6) >> 3) * 8192 + ((((cc + 6) & 7) ^ (lane & 7)) << 4), x1p[12], x1p[13], d0, d1);
    };
    mbar_wait(BAR(c, B_XF), 0);
    if (tid == 128) TS(46);
    load_xslice();
    publish_stats(stats_of<0>(x1p), &g_st[0][st_pub], t, tag);
    if (tid == 0) TS(1);
    LnRow k0, k1;
    {
        const int mi = tid < 224 ? 2 * tid : 0;
        uint4 sa = ld_rlx4(&g_modp[mi]), ca = ld_rlx4(&g_modp[448 + mi]), sb2 = ld_rlx4(&g_modp[2688 + mi]), cb2 = ld_rlx4(&g_modp[2688 + 448 + mi]);
        const float4 s = gather_stats(&g_st[0][st_get + (ws - wq) * 16], tag, 56.0f);
        k0 = ln_row(s.x, s.y); k1 = ln_row(s.z, s.w);
        if (tid == 0) TS(2);
        while (!__all_sync(0xffffffffu, sa.y == tag && sa.w == tag && ca.y == tag && ca.w == tag && sb2.y == tag && sb2.w == tag && cb2.y == tag && cb2.w == tag)) {
            __nanosleep(GATHER_NS);
            sa = ld_rlx4(&g_modp[mi]); ca = ld_rlx4(&g_modp[448 + mi]); sb2 = ld_rlx4(&g_modp[2688 + mi]); cb2 = ld_rlx4(&g_modp[2688 + 448 + mi]);
        }
        const uint32_t c2 = pack_bf16(__uint_as_float(ca.x) + __uint_as_float(cb2.x), __uint_as_float(ca.z) + __uint_as_float(cb2.z));
        if (tid < 224)
            sts64(sb + TAB + (((mi >> 4) * 4 + ((mi & 7) >> 1)) * 2 + ((mi >> 3) & 1)) * 8, pack_bf16(1.0f + bf_lo(c2), 1.0f + bf_hi(c2)),
                  pack_bf16(__uint_as_float(sa.x) + __uint_as_float(sb2.x), __uint_as_float(sa.z) + __uint_as_float(sb2.z)));
    }
    bar_sync(1, 256);
    if (tid == 0) { mbar_arrive(BAR(c, B_GO)); TS(3); }

    uint32_t qa[8], qb[8];
    {
        uint32_t hf[112];
        const uint32_t xb = sb + R0 + wg * 57344 + (uint32_t)(ws * 16 + (lane & 7) + ((lane >> 3) & 1) * 8) * 128;
        const uint32_t xsw = lane & 7, xhi = lane >> 4;
        const int kb0 = (myu * 112) >> 6;
        uint32_t tb = sb + TAB + t * 16 + kb0 * 256, xo = kb0 * 8192;
        const uint32_t dW = dlo(sb + R1, 128);
        uint32_t kvp[30];
        {
            float akv[56];
            uint32_t xa[4];
#pragma unroll
            for (int ks = 0; ks < 4; ks++) { xa[ks] = xb + (((ks * 2 + xhi) ^ xsw) << 4); ldsm4(xa[ks] + xo, hf[4 * ks], hf[4 * ks + 1], hf[4 * ks + 2], hf[4 * ks + 3]); }
            uint4 m0 = lds128(tb), m1 = lds128(tb + 64);
#pragma unroll
            for (int kb = 0; kb < 7; kb++) {
                const uint4 m2 = lds128(tb + 128), m3 = lds128(tb + 192);
#pragma unroll
                for (int ks = 0; ks < 4; ks++) {
                    uint32_t* h = &hf[kb * 16 + ks * 4];
                    const uint4 m = ks == 0 ? m0 : (ks == 1 ? m1 : (ks == 2 ? m2 : m3));
                    h[0] = fma_bf16x2(ln_norm(h[0], k0), m.x, m.y); h[1] = fma_bf16x2(ln_norm(h[1], k1), m.x, m.y);
                    h[2] = fma_bf16x2(ln_norm(h[2], k0), m.z, m.w); h[3] = fma_bf16x2(ln_norm(h[3], k1), m.z, m.w);
                    pin4(h[0], h[1], h[2], h[3]);
                }
                if (kb < 6) {
                    const bool wrap = kb0 + kb == 6;
                    tb += wrap ? -1536 : 256; xo = wrap ? 0 : xo + 8192;
                    asm volatile("" : "+r"(tb), "+r"(xo));
                    if (kb >= 2) mbar_wait(BAR(c, B_XF + kb - 1), 0);
#pragma unroll
                    for (int ks = 0; ks < 4; ks++) { uint32_t* h = &hf[kb * 16 + 16 + ks * 4]; ldsm4(xa[ks] + xo, h[0], h[1], h[2], h[3]); }
                    m0 = lds128(tb); m1 = lds128(tb + 64);
                }
                mbar_wait(BAR(c, B_WKV + kb), 0);
                wg_fence();
#pragma unroll
                for (int ks = 0; ks < 4; ks++) {
                    const uint32_t* h = &hf[kb * 16 + ks * 4];
                    wgmma_rs_n112<H_CM, 1>(akv, h[0], h[1], h[2], h[3], dW + kb * 896 + ks * 16, (kb | ks) != 0);
                }
                wg_commit();
                if (kb == 2 || kb == 4) {
                    wg_wait<1>();
                    if (tw == 0) mbar_arrive(BAR(c, B_KVFREE + (kb >> 2)));
                }
            }
            wg_wait<0>();
            pin(akv);
            const float* ak = akv;
            const float* av = akv + 28;
            load_xslice();
            pin(x1p);
            if (lane == 0) mbar_arrive(BAR(c, B_KVPASS));
            const uint32_t one = t == 0 || t == 2 ? 0x00003F80u : 0u;
#pragma unroll
            for (int j = 0; j < 14; j++) kvp[j] = pack_bf16(ak[2 * j], ak[2 * j + 1]);
#pragma unroll
            for (int j = 0; j < 6; j++) { kvp[14 + j] = pack_bf16(av[2 * j], av[2 * j + 1]); kvp[24 + j] = pack_bf16(av[16 + 2 * j], av[17 + 2 * j]); }
            const uint32_t v30 = pack_bf16(av[12], av[13]), v31 = pack_bf16(av[14], av[15]);
            kvp[20] = t < 2 ? v30 : one; kvp[21] = t < 2 ? v31 : one;
            kvp[22] = t < 2 ? one : v30; kvp[23] = t < 2 ? one : v31;
        }
        if (tid == 0) TS(4);
        float aq[28];
        uint32_t* kvg = reinterpret_cast<uint32_t*>(g_kv + (size_t)gblk * KVB + g_lane_a);
        mbar_wait(BAR(c, B_WQ), 0);
        if (tid == 0) TS(48);
#pragma unroll
        for (int i = 0; i < 7; i++) {
            wg_fence();
#pragma unroll
            for (int ks = 0; ks < 4; ks++) {
                const uint32_t* h = &hf[i * 16 + ks * 4];
                wgmma_rs_n56<H_CM, 1>(aq, h[0], h[1], h[2], h[3], dW + i * 448 + ks * 16, (i | ks) != 0);
            }
            wg_commit();
            if (i < 3) {
#pragma unroll
                for (int j = 5 * i; j < 5 * i + 5; j++) { kvg[j * 256] = kvp[2 * j]; kvg[j * 256 + 32] = kvp[2 * j + 1]; }
            }
            if (i == 2) {
                uint32_t kk[14], vv[16];
#pragma unroll
                for (int j = 0; j < 14; j++) kk[j] = kvp[j];
#pragma unroll
                for (int j = 0; j < 16; j++) vv[j] = kvp[14 + j];
                signal_global(c, B_STKV, lane);
                mbar_wait(BAR(c, B_KVPASS), 0);
                store_cm8<7>(sb + R0 + (4 + wg) * KVB + cm_lane_a, kk);
                store_cm8<8>(sb + R0 + (4 + wg) * KVB + 7168 + cm_lane_a, vv);
                signal_store(c, B_LKV, lane);
                if (tid == 0) TS(50);
            }
        }
        if (c.jb < 112 && wg == 0) {
            silu_vec(sb + WM2_C, c.jb < 56);
            float am[8];
            const uint32_t dA = dlo(sb + WM2_C, 16), dB = dlo(sb + WM2, 16);
#pragma unroll 1
            for (int i = 0; i < 28; i += 2) {
                wg_fence();
                wgmma_ss_n16<0u, (256u >> 4) | (3u << 30), 1>(am, dA + i * 2, dB + i * 32, i != 0);
                wgmma_ss_n16<0u, (256u >> 4) | (3u << 30), 1>(am, dA + i * 2 + 2, dB + i * 32 + 32, 1);
                wg_commit();
            }
            wg_wait<0>();
            pin(am);
            if (tid < 4) { st_rlx4(modq, __float_as_uint(am[0]), tag, __float_as_uint(am[1]), tag); st_rlx4(modq + 8, __float_as_uint(am[4]), tag, __float_as_uint(am[5]), tag); }
            if (tid == 0) TS(37);
        }
        wg_wait<0>();
        pin(aq);
        if (lane == 0) mbar_arrive(BAR(c, B_QPASS));
#pragma unroll
        for (int j = 0; j < 6; j++) { qa[j] = pack_bf16(aq[2 * j] * SM_C, aq[2 * j + 1] * SM_C); qb[2 + j] = pack_bf16(aq[16 + 2 * j] * SM_C, aq[17 + 2 * j] * SM_C); }
        const uint32_t q30 = pack_bf16(aq[12] * SM_C, aq[13] * SM_C), q31 = pack_bf16(aq[14] * SM_C, aq[15] * SM_C);
        qa[6] = t < 2 ? q30 : 0u; qa[7] = t < 2 ? q31 : 0u;
        qb[0] = t < 2 ? 0u : q30; qb[1] = t < 2 ? 0u : q31;
    }
    if (tid == 0) TS(5);

    {
        pin(qa); pin(qb);
        float sA[32], sB[32], oA[16], oB[16];
        uint32_t pA[16], pB[16];
        const bool mk0 = 2 * t <= g, mk1 = 2 * t + 1 <= g;
        uint32_t onall = ((2u << ws) - 1u) | 0xFFF0u | (((0xFu << ws) & 0xFu) << 16);
        if (rb < 4) onall &= (16u << (4 * rb)) - 1u;
        const uint32_t dk0 = uni(dlo(sb + R0 + (4 + wg) * KVB, 1024));
        const uint32_t kv_off = (7168u >> 4) + ((128u >> 4) << 16) - ((1024u >> 4) << 16);
        mbar_wait(BAR(c, B_LKV), 0);
        const uint32_t scr = sb + TAGW + 4;
        {
            wg_fence();
            issue_qk(sA, qa, dk0);
            issue_qk(sB, qb, dk0 + 192);
            wg_commit();
            wg_wait<0>();
            pin(sA); pin(sB);
            cross_mask(sA, true, ws, mk0, mk1);
            cross_mask(sB, true, ws, mk0, mk1);
            float mA0, mA1, mB0, mB1;
#pragma unroll
            for (int r = 0; r < 4; r++) {
                if (r == ws) {
                    mA0 = fmaxf(sA[8 * r], sA[8 * r + 1]); mA1 = fmaxf(fmaxf(sA[8 * r + 2], sA[8 * r + 3]), fmaxf(sA[8 * r + 6], sA[8 * r + 7]));
                    mB0 = fmaxf(sB[8 * r], sB[8 * r + 1]); mB1 = fmaxf(fmaxf(sB[8 * r + 2], sB[8 * r + 3]), fmaxf(sB[8 * r + 6], sB[8 * r + 7]));
                }
            }
            quad_max(mA0, mA1);
            quad_max(mB0, mB1);
            fill_off(sA, onall, mA0, mA1);
            if (tid == 0) TS(62);
            uint32_t dk = dk0, ons = onall;
#pragma unroll 1
            for (int d = 0; d < 5; d++) {
                const int piece = 3 + wg - d;
                const uint32_t dn = d < 4 ? dk - (KVB >> 4) : dk, dv = dk + kv_off;
                exp_block(sA, pA, ons, mA0, mA1, scr);
                wg_wait<0>();
                pin(sB); pin(pA);
                if ((ons & 0xF0u) && piece < 4) mbar_wait(BAR(c, B_KVN + piece), 0);
                wg_fence();
                issue_pv(oA, pA, dv, d);
                issue_qk(sA, qa, dn);
                wg_commit();
                if ((ons & 15u) != 15u || d == 4) { if (d == 4) cross_mask(sB, false, ws, mk0, mk1); fill_off(sB, ons, mB0, mB1); }
                exp_block(sB, pB, ons, mB0, mB1, scr);
                wg_wait<0>();
                pin(sA); pin(pB);
                wg_fence();
                issue_pv(oB, pB, dv + 256, d);
                issue_qk(sB, qb, dn + 192);
                wg_commit();
                dk = dn; ons >>= 4;
                if ((ons & 15u) != 15u || d == 3) { if (d == 3) cross_mask(sA, false, ws, mk0, mk1); fill_off(sA, ons, mA0, mA1); }
                if (tid == 0 && d == 0) TS(51);
            }
            wg_wait<0>();
            pin(oA); pin(oB); pin(sB);
        }
        float lA0 = __shfl_sync(0xffffffffu, oA[12], (lane & 28) | 2), lA1 = __shfl_sync(0xffffffffu, oA[14], (lane & 28) | 2);
        float lB0 = __shfl_sync(0xffffffffu, oB[0], lane & 28), lB1 = __shfl_sync(0xffffffffu, oB[2], lane & 28);
        uint32_t redo;
        asm volatile("{\n.reg .pred p, q;\nsetp.ne.u32 p, %1, 0;\nbar.red.or.pred q, %2, 128, p;\nselp.u32 %0, 1, 0, q;\n}"
                     : "=r"(redo) : "r"((uint32_t)!(fmaxf(fmaxf(lA0, lA1), fmaxf(lB0, lB1)) < 16777216.0f && lA0 + lA1 + lB0 + lB1 < 67108864.0f)), "r"(2 + wg) : "memory");
        if (__builtin_expect(redo, 0)) {
#pragma unroll 1
            for (int h = 0; h < 2; h++) {
                uint32_t q[8];
#pragma unroll
                for (int i = 0; i < 8; i++) q[i] = h ? qb[i] : qa[i];
#pragma unroll
                for (int i = 0; i < 16; i++) oB[i] = 0.f;
                float m0 = -INFINITY, m1 = -INFINITY;
                uint32_t dk = dk0 + h * 192, ons = onall;
#pragma unroll 1
                for (int d = 0; d < 5; d++) {
                    pin(q);
                    wg_fence();
                    issue_qk(sA, q, dk);
                    wg_commit();
                    wg_wait<0>();
                    pin(sA);
                    if ((d & 3) == 0) cross_mask(sA, d == 0, ws, mk0, mk1);
                    fill_off(sA, ons, -INFINITY, -INFINITY);
                    float x0 = m0, x1 = m1;
#pragma unroll
                    for (int j = 0; j < 8; j++) { x0 = fmaxf(x0, fmaxf(sA[4 * j], sA[4 * j + 1])); x1 = fmaxf(x1, fmaxf(sA[4 * j + 2], sA[4 * j + 3])); }
                    quad_max(x0, x1);
                    const float a0 = ex2(m0 - x0), a1 = ex2(m1 - x1);
                    m0 = x0; m1 = x1;
#pragma unroll
                    for (int j = 0; j < 4; j++) { oB[4 * j] *= a0; oB[4 * j + 1] *= a0; oB[4 * j + 2] *= a1; oB[4 * j + 3] *= a1; }
                    exp_block(sA, pA, 15u, x0, x1, scr);
                    pin(oB); pin(pA);
                    wg_fence();
                    issue_pv(oB, pA, dk + kv_off + h * 64, 1);
                    wg_commit();
                    wg_wait<0>();
                    pin(oB);
                    dk -= KVB >> 4; ons >>= 4;
                }
                if (h == 0) {
#pragma unroll
                    for (int i = 0; i < 16; i++) oA[i] = oB[i];
                }
            }
            lA0 = __shfl_sync(0xffffffffu, oA[12], (lane & 28) | 2); lA1 = __shfl_sync(0xffffffffu, oA[14], (lane & 28) | 2);
            lB0 = __shfl_sync(0xffffffffu, oB[0], lane & 28); lB1 = __shfl_sync(0xffffffffu, oB[2], lane & 28);
        }
        const float iA0 = __fdividef(1.0f, lA0), iA1 = __fdividef(1.0f, lA1), iB0 = __fdividef(1.0f, lB0), iB1 = __fdividef(1.0f, lB1);
        uint32_t op[14];
#pragma unroll
        for (int j = 0; j < 3; j++) {
            op[2 * j] = pack_bf16(oA[4 * j] * iA0, oA[4 * j + 1] * iA0); op[2 * j + 1] = pack_bf16(oA[4 * j + 2] * iA1, oA[4 * j + 3] * iA1);
            op[8 + 2 * j] = pack_bf16(oB[4 * j + 4] * iB0, oB[4 * j + 5] * iB0); op[9 + 2 * j] = pack_bf16(oB[4 * j + 6] * iB1, oB[4 * j + 7] * iB1);
        }
        op[6] = t < 2 ? pack_bf16(oA[12] * iA0, oA[13] * iA0) : pack_bf16(oB[0] * iB0, oB[1] * iB0);
        op[7] = t < 2 ? pack_bf16(oA[14] * iA1, oA[15] * iA1) : pack_bf16(oB[2] * iB1, oB[3] * iB1);
        store_cm8_g<7, 2048>(g_o + (size_t)c.b * 14336 + wg * 1024 + g_lane_a, op);
        signal_global(c, B_STO, lane);
        arrive_both(c, B_ATT, lane);
        if (tid == 0) TS(61);
        mbar_wait(BAR(c, B_ATT), 0);
        store_cm8<7, 2048>(sb + R0 + tn * 14336 + cm_lane_a + cm2, op);
        signal_store(c, B_LO, lane);
    }
    if (tid == 0) TS(6);
    if (c.jb < 112) {
        float au[8], av[8];
#pragma unroll
        for (int e = 0; e < 8; e++) { au[e] = 0.f; av[e] = 0.f; }
        unsigned char* wdst = g_winp + (size_t)(c.jb / 7) * (4 * 25088) + ((c.jb % 7) * 2 + (tid & 1)) * 1792;
        mbar_wait(BAR(c, B_WS), 0);
#pragma unroll 1
        for (int row = tid >> 1; row < 448; row += 128) {
            const uint4 wv = lds128(sb + WS_IN + row * 32 + (tid & 1) * 16);
            float2 ps = lds64f(sb + WS_PK + row * 8), pc = lds64f(sb + WS_PK + 3584 + row * 8);
            if (__builtin_expect(__float_as_uint(ps.y) != tag || __float_as_uint(pc.y) != tag, 0)) {
                uint2 us, uc;
                do { us = ld_rlx2(&g_modp[1344 + row]); uc = ld_rlx2(&g_modp[1792 + row]); } while (us.y != tag || uc.y != tag);
                ps.x = __uint_as_float(us.x); pc.x = __uint_as_float(uc.x);
            }
            const float a = 1.0f + bf_round(pc.x), s = 0.5f * bf_round(ps.x);
            const uint32_t a2 = pack_bf16(a, a);
            const uint32_t o0 = fma_bf16x2(wv.x, a2, 0x80008000u), o1 = fma_bf16x2(wv.y, a2, 0x80008000u);
            const uint32_t o2 = fma_bf16x2(wv.z, a2, 0x80008000u), o3 = fma_bf16x2(wv.w, a2, 0x80008000u);
            const int un = row / 112;
            *reinterpret_cast<uint4*>(wdst + un * 25088 + (row - un * 112) * 16) = make_uint4(o0, o1, o2, o3);
            au[0] += bf_lo(o0); au[1] += bf_hi(o0); au[2] += bf_lo(o1); au[3] += bf_hi(o1);
            au[4] += bf_lo(o2); au[5] += bf_hi(o2); au[6] += bf_lo(o3); au[7] += bf_hi(o3);
            av[0] = fmaf(s, bf_lo(wv.x), av[0]); av[1] = fmaf(s, bf_hi(wv.x), av[1]); av[2] = fmaf(s, bf_lo(wv.y), av[2]); av[3] = fmaf(s, bf_hi(wv.y), av[3]);
            av[4] = fmaf(s, bf_lo(wv.z), av[4]); av[5] = fmaf(s, bf_hi(wv.z), av[5]); av[6] = fmaf(s, bf_lo(wv.w), av[6]); av[7] = fmaf(s, bf_hi(wv.w), av[7]);
        }
        const bool b4 = lane & 16, b3 = lane & 8, b2 = lane & 4, b1 = lane & 2;
#pragma unroll
        for (int e = 0; e < 8; e++) { float snd = b4 ? au[e] : av[e], kp = b4 ? av[e] : au[e]; au[e] = kp + __shfl_xor_sync(0xffffffffu, snd, 16); }
#pragma unroll
        for (int e = 0; e < 4; e++) { float snd = b3 ? au[e] : au[e + 4], kp = b3 ? au[e + 4] : au[e]; au[e] = kp + __shfl_xor_sync(0xffffffffu, snd, 8); }
#pragma unroll
        for (int e = 0; e < 2; e++) { float snd = b2 ? au[e] : au[e + 2], kp = b2 ? au[e + 2] : au[e]; au[e] = kp + __shfl_xor_sync(0xffffffffu, snd, 4); }
        { float snd = b1 ? au[0] : au[1], kp = b1 ? au[1] : au[0]; au[0] = kp + __shfl_xor_sync(0xffffffffu, snd, 2); }
        sts32(sb + TAB + tid * 4, __float_as_uint(au[0]));
        bar_sync(1, 256);
        if (warp == 0) {
            float v = 0.f;
#pragma unroll
            for (int w = 0; w < 8; w++) v += lds32f(sb + TAB + w * 128 + lane * 4);
            const int col = (lane & 1) * 8 + (b3 ? 4 : 0) + (b2 ? 2 : 0) + (b1 ? 1 : 0);
            reinterpret_cast<float*>(g_uv)[(c.jb * 8 + (col >> 1)) * 4 + (b4 ? 2 : 0) + (col & 1)] = v;
        }
    }
    signal_store(c, B_STW, lane);

    {
        float ac[28];
        const uint32_t dA = dlo(sb + R0 + wg * 1024, 2048), dW = dlo(sb + R1, 8192);
        mbar_wait(BAR(c, B_WO), 0);
        mbar_wait(BAR(c, B_LO), 0);
#pragma unroll 1
        for (int ui = 0; ui < 4; ui++) {
            const int u = (myu + ui) & 3;
            mbar_wait(BAR(c, B_OF + u), 0);
            if (tid == 0 && (ui & 1) == 0) TS(52 + (ui >> 1));
            if (ui == 0 && tid == 0) mbar_arrive_cl(c.peer_sb + MISC + 8 * B_ORD);
            wg_fence();
#pragma unroll
            for (int ks = 0; ks < 7; ks++) wgmma_ss_n56<H_CK, H_SW, 1>(ac, dA + u * 1792 + ks * 256, dW + u * 896 + ks * 128, (ui | ks) != 0);
            wg_commit();
        }
        mbar_wait(BAR(c, B_GT), 0);
        mbar_wait(BAR(c, B_ORD), 0);
        wg_wait<0>();
        pin(ac);
        arrive_both(c, B_C1D, lane);
        if (tid == 0) TS(7);
        resid(x1p, ac, sb + GTAB + t * 8);
        store_cm8_g<7, 2048>(g_x1 + (size_t)c.b * 14336 + wg * 1024 + g_lane, x1p);
        signal_global(c, B_STX1, lane);
        store_cm8<7, 2048>(sb + R0 + tn * 14336 + cm_lane + cm2, x1p);
        signal_store(c, B_LX1, lane);
        publish_stats(stats_of<0>(x1p), &g_st[1][st_pub], t, tag);
    }
    if (tid == 0) TS(8);

    uint32_t z1p[28];
    const float bs0 = __bfloat162float(p.bsp[row0]), bs1 = __bfloat162float(p.bsp[row0 + 8]);
    {
        float ac[56];
        const uint32_t dA = dlo(sb + R0 + wg * 1024, 2048), dW = dlo(sb + R1, 128);
        float r0, nm0, r1, nm1;
        mbar_wait(BAR(c, B_LX1), 0);
#pragma unroll 1
        for (int q = 0; q < 4; q++) {
            const int u = (myu + q) & 3, slot = (q + 2) & 3;
            mbar_wait(BAR(c, B_X1F + u), 0);
            mbar_wait(BAR(c, B_WINF + slot), 0);
            if (tid == 0) TS(54 + q);
            wg_fence();
#pragma unroll
            for (int ks = 0; ks < 7; ks++) wgmma_ss_n112<H_CK, H_CW, 1>(ac, dA + u * 1792 + ks * 256, dW + slot * 1792 + ks * 16, (q | ks) != 0);
            wg_commit();
            if (q >= 1) {
                wg_wait<1>();
                if (tw == 0) mbar_arrive(BAR(c, B_WINE + ((q + 1) & 3)));
            }
            if (q == 0) {
                const float4 s = gather_stats(&g_st[1][st_get], tag, 56.0f);
                r0 = 0.5f * rsqrtf(s.y + 1e-5f); nm0 = -s.x * r0; r1 = 0.5f * rsqrtf(s.w + 1e-5f); nm1 = -s.z * r1;
            }
        }
        mbar_wait(BAR(c, B_UV), 0);
        wg_wait<0>();
        pin(ac);
        if (tw == 0) mbar_arrive(BAR(c, B_WINE + 1));
        if (tid == 0) TS(10);
        const uint32_t uv = sb + TAB + t * 16;
        float4 zs = make_float4(0.f, 0.f, 0.f, 0.f);
        gelu_blocks<0>(z1p, zs, ac, uv + 896, r0, nm0, r1, nm1);
        if (tid == 0) TS(47);
        gelu_blocks<7>(z1p, zs, ac, uv + 896, r0, nm0, r1, nm1);
#pragma unroll
        for (int sft = 1; sft <= 2; sft <<= 1) {
            zs.x += __shfl_xor_sync(0xffffffffu, zs.x, sft); zs.y += __shfl_xor_sync(0xffffffffu, zs.y, sft);
            zs.z += __shfl_xor_sync(0xffffffffu, zs.z, sft); zs.w += __shfl_xor_sync(0xffffffffu, zs.w, sft);
        }
        zs.x *= 1.0f / 112; zs.z *= 1.0f / 112;
        zs.y = fmaxf(fmaf(-112.0f * zs.x, zs.x, zs.y), 0.f); zs.w = fmaxf(fmaf(-112.0f * zs.z, zs.z, zs.w), 0.f);
        publish_stats(zs, &g_st[2][st_pub], t, tag);
        if (tid == 0) TS(11);
#pragma unroll 1
        for (int q = 4; q < 8; q++) {
            const int u = (myu + q) & 3, slot = (q + 2) & 3;
            mbar_wait(BAR(c, B_WINF + slot), 1);
            wg_fence();
#pragma unroll
            for (int ks = 0; ks < 7; ks++) wgmma_ss_n112<H_CK, H_CW, 1>(ac, dA + u * 1792 + ks * 256, dW + slot * 1792 + ks * 16, (q != 4) || (ks != 0));
            wg_commit();
            if (q == 5) {
                const float4 s = gather_stats(&g_st[2][st_get], tag, 112.0f);
                k0 = ln_row(s.x, s.y); k1 = ln_row(s.z, s.w);
#pragma unroll
                for (int j = 0; j < 28; j++) z1p[j] = ln_norm(z1p[j], (j & 1) ? k1 : k0);
                store_cm8_g<14>(g_z2n + (size_t)(tn * 32 + rb) * 14336 + g_lane, z1p);
                signal_global(c, B_STZ2, lane);
                if (tid == 0) TS(9);
            }
        }
        wg_wait<0>();
        pin(ac);
        arrive_both(c, B_C2D, lane);
        if (tid == 0) TS(12);
        gelu_blocks<0>(z1p, zs, ac, uv, r0, nm0, r1, nm1);
        gelu_blocks<7>(z1p, zs, ac, uv, r0, nm0, r1, nm1);
        pin(z1p);
    }
    if (tid == 0) TS(13);

    {
        float ac[56];
        const uint32_t dA = dlo(sb + wg * 8192, 16), dB = dlo(sb + 16384, 128);
        const uint32_t de = (tw == 0 ? c.self_cl : c.peer_sb) + MISC + 8 * B_DE;
        int s = 0, ps = DSTAGES - 1;
        uint32_t ph = 0;
#pragma unroll 1
        for (int kb = 0; kb < 32; kb++) {
            mbar_wait(BAR(c, B_DF + s), ph);
            if (kb == 0 && tid == 0) TS(45);
            const uint32_t so = s * (DSTAGE >> 4);
            wg_fence();
#pragma unroll
            for (int ks = 0; ks < 4; ks++) wgmma_ss_n112<H_SW, H_CM, 1>(ac, dA + so + ks * 2, dB + so + ks * 16, (kb | ks) != 0);
            wg_commit();
            wg_wait<1>();
            if (kb > 0 && tw < 2) mbar_arrive_cl(de + 8 * ps);
            ps = s;
            if (++s == DSTAGES) { s = 0; ph ^= 1; }
        }
        wg_wait<0>();
        pin(ac);
        arrive_both(c, B_DD, lane);
        if (tid == 0) TS(14);
#pragma unroll
        for (int j = 0; j < 14; j++) {
            z1p[2 * j] = pack_bf16(bf_lo(z1p[2 * j]) * (ac[4 * j] + bs0), bf_hi(z1p[2 * j]) * (ac[4 * j + 1] + bs0));
            z1p[2 * j + 1] = pack_bf16(bf_lo(z1p[2 * j + 1]) * (ac[4 * j + 2] + bs1), bf_hi(z1p[2 * j + 1]) * (ac[4 * j + 3] + bs1));
        }
        store_cm8_g<14, 2048>(g_u + (size_t)c.b * 28672 + wg * 1024 + g_lane, z1p);
        signal_global(c, B_STU, lane);
        bar_sync(1, 256);
        store_cm8<14, 2048>(sb + c.rank * 28672 + cm_lane + cm2, z1p);
        signal_store(c, B_LU, lane);
    }
    if (tid == 0) TS(15);

    {
        float ac[28];
        const uint32_t dA = dlo(sb + wg * 1024, 2048), dW = dlo(sb + WOUT_BASE, 8192);
        const uint32_t ue = (tw == 0 ? c.self_cl : c.peer_sb) + MISC + 8 * B_UE;
        mbar_wait(BAR(c, B_WOUT), 0);
        mbar_wait(BAR(c, B_LU), 0);
#pragma unroll 1
        for (int i = 0; i < 8; i++) {
            const int slot = i < 2 ? (i ^ c.rank) : (i & 3);
            if (i > 0) mbar_wait(BAR(c, B_UF + i), 0);
            if (i == 7) mbar_wait(BAR(c, B_WOUT + 1), 0);
            if (tid == 0 && i < 5) TS(40 + i);
            if (tid == 0 && i == 7) TS(58);
            wg_fence();
#pragma unroll
            for (int ks = 0; ks < 7; ks++) wgmma_ss_n56<H_CK, H_SW, 1>(ac, dA + slot * 1792 + ks * 256, dW + (7 - i) * 896 + ks * 128, (i | ks) != 0);
            wg_commit();
            if (i <= 3) {
                wg_wait<0>();
                if (tw < 2) mbar_arrive_cl(ue + 8 * slot);
            }
        }
        wg_wait<0>();
        pin(ac);
        if (tid == 0) TS(16);
        resid(x1p, ac, sb + GTAB + 224 + t * 8);
        const uint32_t ost = sb + wg * 14336;
        const uint32_t oaddr = ost + (wq * 16 + (lane & 7) + ((lane >> 3) & 1) * 8) * 112 + (lane >> 4) * 16;
        bar_sync(1, 256);
#pragma unroll
        for (int j = 0; j < 6; j += 2) stsm4(oaddr + j * 16, x1p[2 * j], x1p[2 * j + 1], x1p[2 * j + 2], x1p[2 * j + 3]);
        stsm2(oaddr + 96, x1p[12], x1p[13]);
        fence_async_smem();
        bar_sync(2 + wg, 128);
        if (tw == 0) {
            tma2d_store(&p.out, tn * 56, tm * 128 + wg * 64, ost);
            bulk_commit();
            asm volatile("cp.async.bulk.wait_group.read 0;" ::: "memory");
        }
    }
    if (tid == 0) TS(17);
}

template <class OkF, class GoF>
__device__ __forceinline__ void gather(int lane, uint32_t pending, const uint32_t* fl, uint32_t tag, OkF ok, GoF go) {
    uint32_t v0 = ld_rlx(fl);
    while (true) {
        const bool r = ((pending >> lane) & 1u) && v0 == tag && ok();
        if (r) { fence_async_all(); go(); }
        pending &= ~__ballot_sync(0xffffffffu, r);
        if (!pending) break;
        __nanosleep(POLL_NS);
        v0 = ld_rlx(fl);
    }
}
__device__ __forceinline__ void poll_all(const uint32_t* fl, uint32_t tag) {
    while (!__all_sync(0xffffffffu, ld_rlx(fl) == tag)) __nanosleep(POLL_NS);
    fence_async_all();
}

__device__ __forceinline__ void producer(const Params& p, const Ctx& c) {
    const int lane = threadIdx.x & 31;
    const uint32_t sb = c.sb;
    const int tm = c.tm, tn = c.tn, rank = c.rank, myu = tn >> 1;
    auto load_win = [&](int q) {
        const int slot = (q + 2) & 3;
        mbar_expect_tx(BAR(c, B_WINF + slot), 25088);
        bulk_ld(sb + R1 + slot * 28672, g_winp + (size_t)(((q < 4 ? 8 : 0) + tn) * 4 + ((myu + q) & 3)) * 25088, 25088, BAR(c, B_WINF + slot));
    };
    const int kb0 = (myu * 112) >> 6;
    auto load_x = [&](int i) {
        const int kb = kb0 + i < 7 ? kb0 + i : kb0 + i - 7;
        tma2d_mc(sb + R0 + rank * 57344 + kb * 8192, &p.x, kb * 64, tm * 128 + rank * 64, BAR(c, B_XF + (i < 3 ? 0 : i - 2)));
    };
    if (lane < 5) mbar_expect_tx(BAR(c, B_XF + lane), lane ? 16384 : 3 * 16384);
    if (elect()) {
#pragma unroll 1
        for (int i = 0; i < 3; i++) load_x(i);
    }
    const uint32_t tag = get_tag(c);
    {
        const int qid = tn * 7 + lane - 14;
        poll_all(lane < 14 ? flag_ptr(F_R1, tn * 14 + lane) : flag_ptr(F_R1, tn * 14), tag);
        if (elect()) {
            TS(38);
#pragma unroll 1
            for (int i = 0; i < 7; i++) {
                const int kb = kb0 + i < 7 ? kb0 + i : kb0 + i - 7;
                if (i == 2) mbar_wait(BAR(c, B_GO), 0);
                if (i == 4) mbar_wait(BAR(c, B_WMFREE), 0);
                mbar_expect_tx(BAR(c, B_WKV + i), 14336);
                bulk_ld(sb + R1 + i * 14336, g_wkv + (size_t)(tn * 7 + kb) * 14336, 14336, BAR(c, B_WKV + i));
                if (i >= 2 && i < 6) load_x(i + 1);
            }
            TS(39);
        }
        __syncwarp();
        poll_all(lane >= 14 && lane < 21 ? (qid < 16 ? flag_ptr(F_R1, 112 + qid) : flag_ptr(F_R2, qid - 16)) : flag_ptr(F_R1, tn * 14), tag);
        if (elect()) {
            mbar_expect_tx(BAR(c, B_WQ), 50176);
#pragma unroll 1
            for (int i = 0; i < 7; i++) {
                if ((i & 3) == 0) mbar_wait(BAR(c, B_KVFREE + (i >> 2)), 0);
                bulk_ld(sb + R1 + i * 7168, g_wq + (size_t)(tn * 7 + (kb0 + i < 7 ? kb0 + i : kb0 + i - 7)) * 7168, 7168, BAR(c, B_WQ));
            }
            if (c.jb < 112) {
                mbar_expect_tx(BAR(c, B_WM), 14336);
                tma2d(sb + WM2, &p.wmod16, 896 + c.jb * 16, 0, BAR(c, B_WM));
                tma2d(sb + WM2 + 7168, &p.wmod16, 896 + c.jb * 16, 224, BAR(c, B_WM));
            }
        }
    }
    if (elect()) {
        mbar_wait(BAR(c, B_KVPASS), 0);
        if (c.jb < 112) { mbar_expect_tx(BAR(c, B_C), 896); bulk_ld(sb + WM2_C, p.c, 896, BAR(c, B_C)); }
#pragma unroll 1
        for (int pc = 3; pc >= 0; pc--) {
            const int blk = 2 * tm - 4 + pc;
            if (blk >= 0) {
                if (pc & 1) { poll_flag(flag_ptr(F_KV, (blk >> 1) * 8 + tn), tag); fence_async_all(); }
                mbar_expect_tx(BAR(c, B_KVN + pc), KVB);
                bulk_ld(sb + R0 + pc * KVB, g_kv + (size_t)(blk * 8 + tn) * KVB, KVB, BAR(c, B_KVN + pc));
            }
            if (pc & 1) TS(20 + (pc == 1));
        }
        mbar_wait(BAR(c, B_QPASS), 0);
    }
    __syncwarp();
    poll_all(flag_ptr(F_R3, lane < 4 ? 4 * tn + lane : 32 + 8 * tn + (lane & 7)), tag);
    if (elect()) {
        mbar_expect_tx(BAR(c, B_WO), 57344);
        bulk_ld(sb + R1, g_wo + (size_t)tn * 57344, 57344, BAR(c, B_WO));
#pragma unroll 1
        for (int i = 0; i < 8; i++) l2_prefetch((const unsigned char*)p.wsp_p + c.jb * 65536 + i * 8192, 8192);
    }
#pragma unroll 1
    for (int ph = 0; ph < 2; ph++) {
        mbar_wait(BAR(c, ph == 0 ? B_ATT : B_C1D), 0);
        if (ph == 1 && elect()) load_win(2);
        const int src = 2 * (lane & 3) + rank;
        const uint32_t bar = BAR(c, (ph == 0 ? B_OF : B_X1F) + (lane & 3));
        const unsigned char* gsrc = (ph == 0 ? g_o : g_x1) + (size_t)(tm * 8 + src) * 14336;
        if (lane < 4) mbar_expect_tx(bar, lane == myu ? 14336 : 28672);
        gather(lane, 0xFu & ~(1u << myu), flag_ptr(F_O + ph, tm * 8 + src), tag, []() { return true; }, [&]() {
            bulk_ld_mc(sb + R0 + src * 14336, gsrc, 14336, bar, 3);
        });
        if (lane == 0) TS(22 + ph);
        if (ph == 0) {
            mbar_wait(BAR(c, B_HELP), 0);
            poll_all(flag_ptr(F_WP, lane < 7 ? 7 * tn + lane : 49 + 7 * tn + (lane < 14 ? lane : 7)), tag);
            if (elect()) {
                load_win(0);
                load_win(1);
                mbar_expect_tx(BAR(c, B_UV), 1792);
                bulk_ld(sb + TAB, &g_uv[tn * 56], 896, BAR(c, B_UV));
                bulk_ld(sb + TAB + 896, &g_uv[448 + tn * 56], 896, BAR(c, B_UV));
                TS(28);
            }
            __syncwarp();
        }
    }
    if (elect()) {
#pragma unroll 1
        for (int q = 3; q < 8; q++) {
            if (q >= 4) mbar_wait(BAR(c, B_WINE + ((q + 2) & 3)), 0);
            load_win(q);
        }
        mbar_wait(BAR(c, B_C2D), 0);
        TS(24);
#pragma unroll 1
        for (int kb = 0; kb < 3; kb++) {
            mbar_expect_tx(BAR(c, B_DF + kb), DSTAGE);
            tma2d_mc(sb + kb * DSTAGE + rank * 8192, &p.wsp, kb * 64, tm * 128 + rank * 64, BAR(c, B_DF + kb));
        }
    }
    __syncwarp();
    {
        const uint32_t* fl = flag_ptr(F_Z2, lane);
        auto all4 = [&]() { return (ld_rlx(fl) ^ tag) | (ld_rlx(fl + 256) ^ tag) | (ld_rlx(fl + 512) ^ tag) | (ld_rlx(fl + 768) ^ tag); };
        uint32_t v0 = all4();
        while (!__all_sync(0xffffffffu, v0 == 0)) { __nanosleep(POLL_NS); v0 = all4(); }
        fence_async_all();
    }
    if (elect()) {
        TS(25);
        const unsigned char* zsrc = g_z2n + (size_t)tn * 32 * 14336;
        int s = 0;
        uint32_t ph = 1;
#pragma unroll 1
        for (int kb = 0; kb < 32; kb++) {
            if (kb >= 3) {
                mbar_wait(BAR(c, B_DE + s), ph);
                mbar_expect_tx(BAR(c, B_DF + s), DSTAGE);
                tma2d_mc(sb + s * DSTAGE + rank * 8192, &p.wsp, kb * 64, tm * 128 + rank * 64, BAR(c, B_DF + s));
            }
            bulk_ld(sb + s * DSTAGE + 16384, zsrc + (size_t)kb * 14336, 14336, BAR(c, B_DF + s));
            if (++s == DSTAGES) { s = 0; ph ^= 1; }
        }
        mbar_expect_tx(BAR(c, B_WOUT), 7 * 14336);
        mbar_expect_tx(BAR(c, B_WOUT + 1), 14336);
#pragma unroll 1
        for (int k = 0; k < 8; k++) {
            const int i = k == 0 ? 0 : (k == 7 ? 7 : 7 - k);
            if (k == 1 || k == 2 || k == 4) mbar_wait(BAR(c, B_DE + 4 + (k >> 1)), 1);
            if (k == 7) { mbar_wait(BAR(c, B_DD), 0); TS(26); mbar_wait(BAR(c, B_PUB), 0); }
            const int ch = i < 2 ? (tn ^ i) : 2 * ((myu + (i >> 1)) & 3) + (i & 1);
            bulk_ld(sb + WOUT_BASE + (7 - i) * 14336, g_wout + (size_t)(tn * 8 + ch) * 14336, 14336, BAR(c, B_WOUT + (k == 7)));
        }
    }
    __syncwarp();
    {
        const int j = lane & 3, i = 2 * j + rank, ch = 2 * ((myu + j) & 3) + rank, slot = i & 3;
        if (lane >= 1 && lane < 8) mbar_expect_tx(BAR(c, B_UF + lane), 28672);
        __syncwarp();
        const uint32_t bar = BAR(c, B_UF + i), dst = sb + slot * 28672;
        const unsigned char* gsrc = g_u + (size_t)(tm * 8 + ch) * 28672;
        gather(lane, 0xEu, flag_ptr(F_U, tm * 8 + ch), tag, [&]() { return j < 2 || mbar_test(BAR(c, B_UE + slot), 0); }, [&]() {
            bulk_ld_mc(dst, gsrc, 28672, bar, 3);
        });
    }
    if (lane == 0) TS(27);
}

__device__ __forceinline__ void retile_finish(const Ctx& c, uint32_t parity, unsigned char* dst, uint32_t src, uint32_t bytes) {
    mbar_wait(BAR(c, B_RT), parity);
    bulk_st(dst, src, bytes);
    bulk_commit(); bulk_wait_release();
}
__device__ __forceinline__ void retile_qkv_load(const Params& p, const Ctx& c, int job) {
    const int id = job < 112 ? job >> 1 : job - 112, tn = id / 7, kb = id - tn * 7;
    mbar_expect_tx(BAR(c, B_RT), 7168);
    tma2d(c.sb + RT_A, &p.wqkv, (job < 112 ? 448 + (job & 1) * 448 : 0) + tn * 56, kb * 64, BAR(c, B_RT));
}
__device__ __forceinline__ void storer(const Params& p, const Ctx& c, int lane) {
    const uint32_t sb = c.sb, tag = get_tag(c);
    const int b = c.jb;
    uint32_t par = 0;
#pragma unroll 1
    for (int job = b; job < 168; job += 128) {
        mbar_wait(BAR(c, B_RT), par);
        par ^= 1;
        if (lane == 0 && job < 128) TS(60);
        uint4* dst = reinterpret_cast<uint4*>(job < 112 ? g_wkv + (size_t)job * 7168 : g_wq + (size_t)(job - 112) * 7168) + lane;
#pragma unroll 1
        for (int h = 0; h < 2; h++) {
            uint4 v[7];
#pragma unroll
            for (int ch = 0; ch < 7; ch++) v[ch] = lds128(sb + RT_A + (h * 32 + lane) * 112 + ch * 16);
#pragma unroll
            for (int ch = 0; ch < 7; ch++) dst[ch * 64 + h * 32] = v[ch];
        }
        fence_async_smem();
        __syncwarp();
        if (lane == 0) {
            if (job < 40) retile_qkv_load(p, c, job + 128);
            fence_gpu();
            st_rlx(flag_ptr(job < 128 ? F_R1 : F_R2, b), tag);
            if (job < 128) TS(59);
        }
        __syncwarp();
    }
    if (lane == 0) {
        mbar_arrive(BAR(c, B_WMFREE));
#pragma unroll 1
        for (int k = 0; k < 5; k++) {
            mbar_wait(BAR(c, B_STKV + k), 0);
            fence_gpu();
            if (k == F_Z2) mbar_wait(BAR(c, B_C2D), 0);
            st_rlx(flag_ptr(k, c.b), tag);
            TS(30 + k);
            mbar_arrive(BAR(c, B_PUB));
            if (k == F_KV) {
                if (b < 96) {
                    const int id = b < 32 ? b : b - 32;
                    mbar_wait(BAR(c, B_KVPASS), 0);
                    mbar_expect_tx(BAR(c, B_RT), 112 * 112);
                    tma2d(sb + RT_B, b < 32 ? &p.wo : &p.wout, (b < 32 ? id >> 2 : id >> 3) * 56, (b < 32 ? id & 3 : id & 7) * 112, BAR(c, B_RT));
                    retile_finish(c, par, b < 32 ? g_wo + (size_t)b * 14336 : g_wout + (size_t)(b - 32) * 14336, sb + RT_B, 14336);
                    st_rlx(flag_ptr(F_R3, b), tag);
                }
                mbar_arrive(BAR(c, B_HELP));
            }
        }
        if (c.b == 0) st_rlx(&g_epoch, tag);
    }
}

__device__ __forceinline__ void helper(const Params& p, const Ctx& c) {
    const int lane = threadIdx.x & 31;
    const uint32_t sb = c.sb, tag = get_tag(c);
    mbar_wait(BAR(c, B_QPASS), 0);
    {
        const uint2* wp = &g_modp[896 + lane * 16 + 15];
        while (!__all_sync(0xffffffffu, (ld_rlx2(wp).y == tag) & (ld_rlx2(wp + 512).y == tag) & (ld_rlx2(wp + 1024).y == tag) & (ld_rlx2(wp + (lane < 16 ? 1536 : 0)).y == tag)))
            __nanosleep(6 * POLL_NS);
    }
    if (lane == 0 && c.jb < 112) {
        fence_async_all();
        mbar_expect_tx(BAR(c, B_WS), 14336 + 7168);
        bulk_ld(sb + WS_PK, &g_modp[1344], 7168, BAR(c, B_WS));
        tma2d(sb + WS_IN, &p.wins, c.jb * 16, 0, BAR(c, B_WS));
        tma2d(sb + WS_IN + 7168, &p.wins, c.jb * 16, 224, BAR(c, B_WS));
    }
    if (lane < 28) {
        uint4 ga, gb;
        while (true) {
            ga = ld_rlx4(&g_modp[896 + c.tn * 56 + 2 * lane]); gb = ld_rlx4(&g_modp[2240 + c.tn * 56 + 2 * lane]);
            if (ga.y == tag && ga.w == tag && gb.y == tag && gb.w == tag) break;
        }
        sts64(sb + GTAB + lane * 8, __float_as_uint(bf_round(__uint_as_float(ga.x))), __float_as_uint(bf_round(__uint_as_float(ga.z))));
        sts64(sb + GTAB + 224 + lane * 8, __float_as_uint(bf_round(__uint_as_float(gb.x))), __float_as_uint(bf_round(__uint_as_float(gb.z))));
    }
    __syncwarp();
    if (lane == 0) {
        mbar_arrive(BAR(c, B_GT));
#pragma unroll 1
        for (int k = 0; k < 3; k++) {
            mbar_wait(BAR(c, B_LO + k), 0);
            if (k) mbar_wait(BAR(c, k == 1 ? B_C1D : B_DD), 0);
            if (k == 2) mbar_wait(BAR(c, B_PUB), 0);
            const uint32_t off = k == 2 ? c.rank * 28672 : R0 + c.tn * 14336;
            bulk_push(c.peer_sb + off, sb + off, k == 2 ? 28672 : 14336, c.peer_sb + MISC + 8 * (k == 2 ? B_UF + 1 : (k ? B_X1F : B_OF) + (c.tn >> 1)));
            if (k == 0) {
                mbar_wait(BAR(c, B_STW), 0);
                if (c.jb < 112) {
                    fence_gpu();
                    st_rlx(flag_ptr(F_WP, c.jb), tag);
                    TS(29);
                }
                mbar_arrive(BAR(c, B_HELP));
            }
        }
    }
}

template <int LO, int HI> __device__ __forceinline__ void init_bars(const Ctx& c) {
#pragma unroll
    for (int i = LO; i < HI; i++) mbar_init(BAR(c, i), bar_count(i));
    asm volatile("fence.mbarrier_init.release.cluster;" ::: "memory");
}

__global__ void __cluster_dims__(2, 1, 1) __launch_bounds__(NTHREADS, 1) fused_block_kernel(const __grid_constant__ Params p) {
    extern __shared__ __align__(1024) unsigned char smem[];
    const int tid = threadIdx.x, warp = tid >> 5, lane = tid & 31;
    Ctx c;
    c.sb = uni(smem_u32(smem));
    c.rank = blockIdx.x & 1;
    c.jb = blockIdx.x;
    c.self_cl = mapa(c.sb, c.rank);
    c.peer_sb = mapa(c.sb, c.rank ^ 1);
    if (warp < 8) {
        asm volatile("setmaxnreg.inc.sync.aligned.u32 232;");
        cluster_arrive_relaxed();
        consumer(p, c);
        if (lane == 0) mbar_arrive(BAR(c, B_DONE));
        cluster_arrive_relaxed();
        cluster_wait();
    } else {
        asm volatile("setmaxnreg.dec.sync.aligned.u32 40;");
        uint32_t epoch = 0;
        if (tid == 320) epoch = ld_rlx(&g_epoch);
        if (tid == 256) { if (c.sb & 1023) __trap(); init_bars<0, 36>(c); }
        if (tid == 288) {
            init_bars<B_RT, B_WM>(c);
            retile_qkv_load(p, c, c.jb);
            init_bars<36, 58>(c);
        }
        if (tid == 352) {
            init_bars<B_WM, NBAR>(c);
            if (c.jb < 56) {
                mbar_expect_tx(BAR(c, B_C), 896);
                bulk_ld(c.sb + WM_BASE + 14336, p.c, 896, BAR(c, B_C));
                mbar_expect_tx(BAR(c, B_WM), 14336);
                tma2d(c.sb + WM_BASE, &p.wmod, (c.jb >> 1) * 32, (c.jb & 1) * 224, BAR(c, B_WM));
            }
            init_bars<58, B_RT>(c);
        }
        __syncwarp();
        cluster_arrive_relaxed();
        if (warp == 9 && lane < 2) {
#pragma unroll 1
            for (int k = F_R1; k < F_WP; k++) st_rlx4(flag_ptr(k, c.jb) + lane * 4, 0, 0, 0, 0);
        }
        if (warp == 10 && lane < 2) st_rlx4(flag_ptr(F_WP, c.jb) + lane * 4, 0, 0, 0, 0);
        if (warp == 11 && lane >= 3 && lane < 9) asm volatile("prefetch.tensormap [%0];" ::"l"(&p.wmod + lane) : "memory");
        cluster_wait();
        if (tid == 352) {
            uint32_t smid;
            asm volatile("mov.u32 %0, %%smid;" : "=r"(smid));
            mbar_expect_tx(BAR(c, B_SMID), 4);
            asm volatile("st.async.weak.shared::cluster.mbarrier::complete_tx::bytes.u32 [%0], %1, [%2];" ::"r"(c.peer_sb + TAGW + 8), "r"(smid), "r"(c.peer_sb + MISC + 8 * B_SMID) : "memory");
        }
        asm volatile("" : "+r"(epoch)::"memory");
        if (warp == 10) {
            const uint32_t tag = uni(epoch) + 1;
            if (lane == 0) { sts32(c.sb + TAGW, tag); mbar_arrive(BAR(c, B_TAG)); }
            uint32_t key;
            const uint32_t r = fixed_role(p, c, key);
            if (lane == 0 && c.rank == 0) st_rlx2(&g_here[c.jb >> 1], r == 255u ? key : r, tag);
            if (r == 255u) {
                uint2 h0, h1;
                do { h0 = ld_rlx2(&g_here[lane]); h1 = ld_rlx2(&g_here[32 + lane]); } while (!__all_sync(0xffffffffu, h0.y == tag && h1.y == tag));
                const uint32_t lo = __reduce_or_sync(0xffffffffu, (h0.x < 32 ? 1u << h0.x : 0u) | (h1.x < 32 ? 1u << h1.x : 0u));
                const uint32_t hi = __reduce_or_sync(0xffffffffu, (h0.x >= 32 && h0.x < 64 ? 1u << (h0.x - 32) : 0u) | (h1.x >= 32 && h1.x < 64 ? 1u << (h1.x - 32) : 0u));
                const int n = __popc(__ballot_sync(0xffffffffu, h0.x >= 256 && h0.x < key)) + __popc(__ballot_sync(0xffffffffu, h1.x >= 256 && h1.x < key));
                const int nlo = __popc(~lo);
                if (lane == 0) { sts32(c.sb + TAGW + 12, n < nlo ? __fns(~lo, 0, n + 1) : 32 + __fns(~hi, 0, n - nlo + 1)); mbar_arrive(BAR(c, B_ROLE)); }
                __syncwarp();
            }
        }
        if (warp == 11) { watchdog(BAR(c, B_DONE)); return; }
        resolve_role(p, c);
        if (warp == 8) producer(p, c);
        else if (warp == 9) {
            if (lane < 2) {
#pragma unroll 1
                for (int k = 0; k < F_R1; k++) st_rlx4(flag_ptr(k, c.b) + lane * 4, 0, 0, 0, 0);
            }
            storer(p, c, lane);
        } else helper(p, c);
    }
}

typedef CUresult (*EncodeFn)(CUtensorMap*, CUtensorMapDataType, cuuint32_t, void*, const cuuint64_t*, const cuuint64_t*, const cuuint32_t*,
                             const cuuint32_t*, CUtensorMapInterleave, CUtensorMapSwizzle, CUtensorMapL2promotion, CUtensorMapFloatOOBfill);

void make_map(EncodeFn enc, CUtensorMap* m, const void* ptr, uint64_t inner, uint64_t outer, uint32_t bi, uint32_t bo, CUtensorMapSwizzle swz) {
    cuuint64_t dims[2] = {inner, outer};
    cuuint64_t strides[1] = {inner * 2};
    cuuint32_t box[2] = {bi, bo}, es[2] = {1, 1};
    enc(m, CU_TENSOR_MAP_DATA_TYPE_BFLOAT16, 2, const_cast<void*>(ptr), dims, strides, box, es, CU_TENSOR_MAP_INTERLEAVE_NONE, swz,
        CU_TENSOR_MAP_L2_PROMOTION_L2_128B, CU_TENSOR_MAP_FLOAT_OOB_FILL_NONE);
}

}

extern "C" void kernel_launch(void* const* d_in, const int* in_sizes, int n_in, void* d_out, int out_size) {
    static EncodeFn enc = nullptr;
    if (!enc) {
        void* fn = nullptr;
        cudaDriverEntryPointQueryResult st;
        cudaGetDriverEntryPoint("cuTensorMapEncodeTiled", &fn, cudaEnableDefault, &st);
        enc = (EncodeFn)fn;
        cudaFuncSetAttribute(fused_block_kernel, cudaFuncAttributeMaxDynamicSharedMemorySize, SMEM_BYTES);
    }
    Params p;
    make_map(enc, &p.x, d_in[0], 448, 2048, 64, 64, CU_TENSOR_MAP_SWIZZLE_128B);
    make_map(enc, &p.wqkv, d_in[1], 1344, 448, 56, 64, CU_TENSOR_MAP_SWIZZLE_NONE);
    make_map(enc, &p.wo, d_in[2], 448, 448, 56, 112, CU_TENSOR_MAP_SWIZZLE_128B);
    make_map(enc, &p.wins, d_in[4], 1792, 448, 16, 224, CU_TENSOR_MAP_SWIZZLE_NONE);
    make_map(enc, &p.wsp, d_in[5], 2048, 2048, 64, 64, CU_TENSOR_MAP_SWIZZLE_128B);
    make_map(enc, &p.wout, d_in[7], 448, 896, 56, 112, CU_TENSOR_MAP_SWIZZLE_128B);
    make_map(enc, &p.wmod, d_in[9], 2688, 448, 32, 224, CU_TENSOR_MAP_SWIZZLE_64B);
    make_map(enc, &p.wmod16, d_in[9], 2688, 448, 16, 224, CU_TENSOR_MAP_SWIZZLE_32B);
    make_map(enc, &p.out, d_out, 448, 2048, 56, 64, CU_TENSOR_MAP_SWIZZLE_NONE);
    p.c = (const __nv_bfloat16*)d_in[8]; p.bsp = (const __nv_bfloat16*)d_in[6];
    p.wsp_p = (const __nv_bfloat16*)d_in[5];
    for (int i = 0; i < 68; i++) p.role[i] = h_role[i];
    fused_block_kernel<<<128, NTHREADS, SMEM_BYTES>>>(p);
}
```
